```python
import torch

def _softmax(x, axis=-1):
    return torch.softmax(x, dim=axis)
def _gelu(x):
    return torch.nn.functional.gelu(x, approximate="tanh")
def _silu(x):
    return torch.nn.functional.silu(x)
def _sigmoid(x):
    return torch.sigmoid(x)
def _layernorm(x, axis=-1, eps=1e-5):
    m = x.mean(dim=axis, keepdim=True)
    v = x.var(dim=axis, keepdim=True, unbiased=False)
    return (x - m) / torch.sqrt(v + eps)
def _scatter_add(tgt, idx, src, axis=0):
    return tgt.clone().index_add_(axis, idx, src)
def _segment_sum(src, seg, n):
    out = torch.zeros((n,) + src.shape[1:], dtype=src.dtype)
    return out.index_add_(0, seg, src)
def _pad(x, pw):
    flat = tuple(v for pair in reversed(pw) for v in pair)
    return torch.nn.functional.pad(x, flat)

kernel_name = 'gated_mix__sliding_local_dilated__dense_activation_squared_relu__prompt'

def setup_inputs():

    _w = (lambda a: (lambda t: t.to(torch.bfloat16) if t.is_floating_point() else t)(torch.as_tensor(a)))
    def _A_setup():
        B, S, D = 1, 2048, 640
        return {
            "x": _w((lambda *s: torch.randn(*s, dtype=torch.bfloat16) * 0.05)(B, S, D)),
            "wqkv": _w((lambda *s: torch.randn(*s, dtype=torch.bfloat16) * 0.8)(D, 3 * D)),
            "wo": _w((lambda *s: torch.randn(*s, dtype=torch.bfloat16) * 0.05)(D, D)),
        }
    _A_in = _A_setup()

    def _B_setup():
        B, S, D, F = 1, 2048, 640, 1728
        return {
            "x": _w((lambda *s: torch.randn(*s, dtype=torch.bfloat16) * 0.05)(B, S, D)),
            "w1": _w((lambda *s: torch.randn(*s, dtype=torch.bfloat16) * 0.2)(D, F)),
            "b1": _w((lambda *s: torch.randn(*s, dtype=torch.bfloat16) * 0.2)(F)),
            "w2": _w((lambda *s: torch.randn(*s, dtype=torch.bfloat16) * 0.2)(F, D)),
            "b2": _w((lambda *s: torch.randn(*s, dtype=torch.bfloat16) * 0.2)(D)),
        }
    _B_in = _B_setup()

    return {
        "A_x": _A_in["x"],
        "A_wqkv": _A_in["wqkv"],
        "A_wo": _A_in["wo"],
        "B_x": _B_in["x"],
        "B_w1": _B_in["w1"],
        "B_b1": _B_in["b1"],
        "B_w2": _B_in["w2"],
        "B_b2": _B_in["b2"],
        "gate_w": _w((lambda *s: torch.randn(*s, dtype=torch.bfloat16) * 0.05)(640) * 16.0),
    }

def reference(A_x, A_wqkv, A_wo, B_x, B_w1, B_b1, B_w2, B_b2, gate_w):
    def _A_ref(x, wqkv, wo):
        B, S, D = x.shape
        H = 32; Dh = D // H
        W, dil = 8, 2
        qkv = (lambda x, *d: x.permute(*d))((x @ wqkv).reshape(B, S, 3, H, Dh), 2, 0, 3, 1, 4)
        q, k, v = qkv[0], qkv[1], qkv[2]
        scale = Dh ** -0.5
        pos = torch.arange(S)
        off = torch.arange(W) * dil
        idx = pos[:, None] - off[None, :]
        mask = idx >= 0
        idx_c = torch.where(mask, idx, 0).reshape(-1)
        kg = k[:, :, idx_c, :].reshape(B, H, S, W, Dh)
        vg = v[:, :, idx_c, :].reshape(B, H, S, W, Dh)
        logits = torch.einsum("bhsd,bhswd->bhsw", q, kg) * scale
        logits = torch.where(mask[None, None, :, :], logits, -1e9)
        attn = _softmax(logits, axis=-1)
        o = torch.einsum("bhsw,bhswd->bhsd", attn, vg)
        return (lambda x, *d: x.permute(*d))(o, 0, 2, 1, 3).reshape(B, S, D) @ wo

    def _B_ref(x, w1, b1, w2, b2):
        h = torch.einsum("bsd,df->bsf", x, w1) + b1
        zero = torch.zeros_like(h)
        r = torch.where(h > zero, h, zero)
        h = r * r
        out = torch.einsum("bsf,fd->bsd", h, w2) + b2
        return out

    x = A_x
    g = _sigmoid((x * gate_w).sum(-1, keepdims=True))
    a = _A_ref(x, A_wqkv, A_wo)
    b = _B_ref(x, B_w1, B_b1, B_w2, B_b2)
    return g * a + (1 - g) * b
```

```cpp
#include <cuda_runtime.h>
#include <cuda_bf16.h>
#include <cuda.h>
#include <stdint.h>

namespace {

constexpr int SEQ = 2048, DM = 640, FF = 1728;
constexpr int NCTA = 128;
constexpr int NTHREADS = 384;

constexpr uint32_t PAGE = 16384;
constexpr int NA = 4, NW = 7;
constexpr uint32_t WB = NA * PAGE;
constexpr uint32_t R0 = (NA + NW) * PAGE;
constexpr uint32_t PLANE = 72 * 160 + 18 * 16;
constexpr uint32_t BAR_OFF = R0 + 49152;
constexpr uint32_t G_OFF = BAR_OFF + 256;
constexpr uint32_t BIAS_OFF = G_OFF + 256;
constexpr uint32_t SMEM_BYTES = BIAS_OFF + 768;
static_assert(SMEM_BYTES <= 232448 && R0 % 1024 == 0 && 4 * PLANE <= 49152, "smem");

enum { B_AF = 0, B_AE = 4, B_WF = 8, B_WE = 15, B_GREADY = 22, B_HDONE = 23, B_HFREE = 24, B_HALO = 25, B_ODONE = 26, B_XG = 27, B_KV = 28, B_NBAR = 29 };
#define NBOX1 24
#define NBOX2 32
constexpr uint32_t BYTES_W1 = 12288 + NBOX1 * 64, BYTES_W2 = 8192 + NBOX2 * 64;
constexpr int N_H = 20, N_QKV = 20, N_P3 = 37;
#define ATTPOS 10
constexpr int ATT_POS = ATTPOS;
#define HPACE 600
constexpr uint32_t H_PACE = HPACE;

struct Params {
  CUtensorMap w[8];
  CUtensorMap a[3];
  CUtensorMap hst, ost, outw, outn;
  const __nv_bfloat16 *pwqkv, *pwo, *pw2;
};

__device__ __align__(1024) __nv_bfloat16 g_H[SEQ * FF];
__device__ __align__(1024) __nv_bfloat16 g_O[SEQ * DM];
__device__ __align__(128) unsigned long long g_gateLL[SEQ];
__device__ __align__(128) uint8_t g_halo[128 * 4 * 1312];
__device__ __align__(128) uint32_t g_flag[16 * 32];
__device__ __align__(128) uint32_t g_done;

#define TR(slot) do {} while (0)
#define TRW(slot) do {} while (0)
__device__ __forceinline__ uint32_t smem_u32(const void* p) { return (uint32_t)__cvta_generic_to_shared(p); }
__device__ __forceinline__ void mbar_init(uint32_t bar, uint32_t cnt) { asm volatile("mbarrier.init.shared::cta.b64 [%0], %1;" ::"r"(bar), "r"(cnt) : "memory"); }
__device__ __forceinline__ void mbar_expect_tx(uint32_t bar, uint32_t bytes) { asm volatile("mbarrier.arrive.expect_tx.shared::cta.b64 _, [%0], %1;" ::"r"(bar), "r"(bytes) : "memory"); }
__device__ __forceinline__ void mbar_arrive(uint32_t bar) { asm volatile("mbarrier.arrive.shared::cta.b64 _, [%0];" ::"r"(bar) : "memory"); }
__device__ __forceinline__ uint32_t mapa(uint32_t addr, uint32_t cta) { uint32_t r; asm volatile("mapa.shared::cluster.u32 %0, %1, %2;" : "=r"(r) : "r"(addr), "r"(cta)); return r; }
__device__ __forceinline__ void mbar_arrive_remote(uint32_t rbar) { asm volatile("mbarrier.arrive.shared::cluster.b64 _, [%0];" ::"r"(rbar) : "memory"); }
constexpr uint32_t SPIN_MAX = 1u << 21;
__device__ __forceinline__ void mbar_wait(uint32_t bar, uint32_t parity, uint32_t& n) {
  asm volatile("{\n.reg .pred p, q;\nLAB_WAIT:\n"
               "mbarrier.try_wait.parity.shared::cta.b64 p, [%1], %2;\n"
               "add.u32 %0, %0, 1;\nsetp.lt.and.u32 q, %0, %3, !p;\n@q bra LAB_WAIT;\n}" : "+r"(n) : "r"(bar), "r"(parity), "n"(SPIN_MAX) : "memory");
}
__device__ __forceinline__ bool elect_one() {
  uint32_t p;
  asm volatile("{\n.reg .pred P;\nelect.sync _|P, 0xffffffff;\nselp.u32 %0, 1, 0, P;\n}" : "=r"(p));
  return p;
}
__device__ __forceinline__ void tma_4d(uint32_t dst, const CUtensorMap* tm, int c0, int c1, int c2, int c3, uint32_t bar) {
  asm volatile("cp.async.bulk.tensor.4d.shared::cluster.global.mbarrier::complete_tx::bytes [%0], [%1, {%3, %4, %5, %6}], [%2];"
               ::"r"(dst), "l"(tm), "r"(bar), "r"(c0), "r"(c1), "r"(c2), "r"(c3) : "memory");
}
__device__ __forceinline__ void tma_4d_mc(uint32_t dst, const CUtensorMap* tm, int c0, int c1, int c2, int c3, uint32_t bar) {
  asm volatile("cp.async.bulk.tensor.4d.shared::cluster.global.mbarrier::complete_tx::bytes.multicast::cluster [%0], [%1, {%3, %4, %5, %6}], [%2], %7;"
               ::"r"(dst), "l"(tm), "r"(bar), "r"(c0), "r"(c1), "r"(c2), "r"(c3), "h"((uint16_t)3) : "memory");
}
__device__ __forceinline__ void tma_store_4d(const CUtensorMap* tm, uint32_t src, int c0, int c1, int c2, int c3) {
  asm volatile("cp.async.bulk.tensor.4d.global.shared::cta.bulk_group [%0, {%2, %3, %4, %5}], [%1];" ::"l"(tm), "r"(src), "r"(c0), "r"(c1), "r"(c2), "r"(c3) : "memory");
}
__device__ __forceinline__ void tma_reduce_4d(const CUtensorMap* tm, uint32_t src, int c0, int c2, int c3) {
  asm volatile("cp.reduce.async.bulk.tensor.4d.global.shared::cta.add.bulk_group [%0, {%2, %5, %3, %4}], [%1];" ::"l"(tm), "r"(src), "r"(c0), "r"(c2), "r"(c3), "r"(0) : "memory");
}
__device__ __forceinline__ void bulk_load(uint32_t dst, const void* src, uint32_t bytes, uint32_t bar) {
  asm volatile("cp.async.bulk.shared::cluster.global.mbarrier::complete_tx::bytes [%0], [%1], %2, [%3];" ::"r"(dst), "l"(src), "r"(bytes), "r"(bar) : "memory");
}
__device__ __forceinline__ void bulk_store(void* dst, uint32_t src, uint32_t bytes) {
  asm volatile("cp.async.bulk.global.shared::cta.bulk_group [%0], [%1], %2;" ::"l"(dst), "r"(src), "r"(bytes) : "memory");
}
__device__ __forceinline__ void l2_prefetch(const void* src, uint32_t bytes) {
  asm volatile("cp.async.bulk.prefetch.L2.global [%0], %1;" ::"l"(src), "r"(bytes) : "memory");
}
__device__ __forceinline__ void prefetch_tmap(const CUtensorMap* tm) { asm volatile("prefetch.tensormap [%0];" ::"l"(tm) : "memory"); }
__device__ __forceinline__ void fence_async_smem() { asm volatile("fence.proxy.async.shared::cta;" ::: "memory"); }
__device__ __forceinline__ void fence_async_glob() { asm volatile("fence.proxy.async.global;" ::: "memory"); }
__device__ __forceinline__ void wg_fence() { asm volatile("wgmma.fence.sync.aligned;" ::: "memory"); }
__device__ __forceinline__ void wg_commit() { asm volatile("wgmma.commit_group.sync.aligned;" ::: "memory"); }
template <int N> __device__ __forceinline__ void wg_wait() { asm volatile("wgmma.wait_group.sync.aligned %0;" ::"n"(N) : "memory"); }
__device__ __forceinline__ uint64_t make_desc(uint32_t addr, uint32_t lbo, uint32_t sbo, uint32_t swz  ) {
  return (uint64_t)((addr & 0x3FFFF) >> 4) | ((uint64_t)(lbo >> 4) << 16) | ((uint64_t)(sbo >> 4) << 32) | ((uint64_t)swz << 62);
}
__device__ __forceinline__ void stmatrix_x4(uint32_t addr, uint32_t a, uint32_t b, uint32_t c, uint32_t d) {
  asm volatile("stmatrix.sync.aligned.m8n8.x4.shared.b16 [%0], {%1, %2, %3, %4};" ::"r"(addr), "r"(a), "r"(b), "r"(c), "r"(d) : "memory");
}
__device__ __forceinline__ void ldsm4(uint32_t* d, uint32_t addr) {
  asm volatile("ldmatrix.sync.aligned.m8n8.x4.shared.b16 {%0, %1, %2, %3}, [%4];" : "=r"(d[0]), "=r"(d[1]), "=r"(d[2]), "=r"(d[3]) : "r"(addr) : "memory");
}
__device__ __forceinline__ void ldsm4t(uint32_t* d, uint32_t addr) {
  asm volatile("ldmatrix.sync.aligned.m8n8.x4.trans.shared.b16 {%0, %1, %2, %3}, [%4];" : "=r"(d[0]), "=r"(d[1]), "=r"(d[2]), "=r"(d[3]) : "r"(addr) : "memory");
}
__device__ __forceinline__ void mma16z(float* d, uint32_t a0, uint32_t a1, uint32_t a2, uint32_t a3, uint32_t b0, uint32_t b1) {
  asm volatile("mma.sync.aligned.m16n8k16.row.col.f32.bf16.bf16.f32 {%0, %1, %2, %3}, {%4, %5, %6, %7}, {%8, %9}, {%10, %10, %10, %10};"
               : "=f"(d[0]), "=f"(d[1]), "=f"(d[2]), "=f"(d[3]) : "r"(a0), "r"(a1), "r"(a2), "r"(a3), "r"(b0), "r"(b1), "f"(0.f));
}
__device__ __forceinline__ void mma16(float* d, uint32_t a0, uint32_t a1, uint32_t a2, uint32_t a3, uint32_t b0, uint32_t b1) {
  asm volatile("mma.sync.aligned.m16n8k16.row.col.f32.bf16.bf16.f32 {%0, %1, %2, %3}, {%4, %5, %6, %7}, {%8, %9}, {%0, %1, %2, %3};"
               : "+f"(d[0]), "+f"(d[1]), "+f"(d[2]), "+f"(d[3]) : "r"(a0), "r"(a1), "r"(a2), "r"(a3), "r"(b0), "r"(b1));
}
__device__ __forceinline__ void mma8z(float* d, uint32_t a0, uint32_t a1, uint32_t b0) {
  asm volatile("mma.sync.aligned.m16n8k8.row.col.f32.bf16.bf16.f32 {%0, %1, %2, %3}, {%4, %5}, {%6}, {%7, %7, %7, %7};"
               : "=f"(d[0]), "=f"(d[1]), "=f"(d[2]), "=f"(d[3]) : "r"(a0), "r"(a1), "r"(b0), "f"(0.f));
}
__device__ __forceinline__ void mma8(float* d, uint32_t a0, uint32_t a1, uint32_t b0) {
  asm volatile("mma.sync.aligned.m16n8k8.row.col.f32.bf16.bf16.f32 {%0, %1, %2, %3}, {%4, %5}, {%6}, {%0, %1, %2, %3};"
               : "+f"(d[0]), "+f"(d[1]), "+f"(d[2]), "+f"(d[3]) : "r"(a0), "r"(a1), "r"(b0));
}
__device__ __forceinline__ uint32_t pack_bf16(float lo, float hi) {
  uint32_t r; asm("cvt.rn.bf16x2.f32 %0, %1, %2;" : "=r"(r) : "f"(hi), "f"(lo)); return r;
}
__device__ __forceinline__ uint32_t pack_bf16_relu(float lo, float hi) {
  uint32_t r; asm("cvt.rn.relu.bf16x2.f32 %0, %1, %2;" : "=r"(r) : "f"(hi), "f"(lo)); return r;
}
__device__ __forceinline__ uint32_t add_relu_bf16x2(uint32_t a, uint32_t b) {
  uint32_t r; asm("fma.rn.relu.bf16x2 %0, %1, %2, %3;" : "=r"(r) : "r"(a), "r"(0x3f803f80u), "r"(b)); return r;
}
__device__ __forceinline__ uint32_t fma_bf16x2(uint32_t a, uint32_t b, uint32_t c) {
  uint32_t r; asm("fma.rn.bf16x2 %0, %1, %2, %3;" : "=r"(r) : "r"(a), "r"(b), "r"(c)); return r;
}
__device__ __forceinline__ void prefetch_l2(const void* p) { asm volatile("prefetch.global.L2 [%0];" ::"l"(p)); }
__device__ __forceinline__ uint32_t mul_bf16x2(uint32_t a, uint32_t b) {
  uint32_t r; asm("mul.rn.bf16x2 %0, %1, %2;" : "=r"(r) : "r"(a), "r"(b)); return r;
}
__device__ __forceinline__ float bf_lo(uint32_t w) { return __uint_as_float(w << 16); }
__device__ __forceinline__ float bf_hi(uint32_t w) { return __uint_as_float(w & 0xffff0000u); }
__device__ __forceinline__ uint32_t lds16(uint32_t a) { uint16_t v; asm volatile("ld.shared.u16 %0, [%1];" : "=h"(v) : "r"(a)); return v; }
__device__ __forceinline__ void sts16(uint32_t a, uint16_t v) { asm volatile("st.shared.u16 [%0], %1;" ::"r"(a), "h"(v) : "memory"); }
__device__ __forceinline__ uint32_t ld_acquire(const uint32_t* p) { uint32_t v; asm volatile("ld.acquire.gpu.global.u32 %0, [%1];" : "=r"(v) : "l"(p) : "memory"); return v; }
__device__ __forceinline__ void st_flag(uint32_t* p, uint32_t v) { asm volatile("st.relaxed.gpu.global.u32 [%0], %1;" ::"l"(p), "r"(v) : "memory"); }
__device__ __forceinline__ float ex2(float x) { float r; asm("ex2.approx.ftz.f32 %0, %1;" : "=f"(r) : "f"(x)); return r; }
__device__ __forceinline__ float rcp(float x) { float r; asm("rcp.approx.ftz.f32 %0, %1;" : "=f"(r) : "f"(x)); return r; }
__device__ __forceinline__ uint64_t ld_ll(const unsigned long long* p) { uint64_t v; asm volatile("ld.relaxed.gpu.global.b64 %0, [%1];" : "=l"(v) : "l"(p) : "memory"); return v; }
__device__ __forceinline__ void st_ll(unsigned long long* p, uint32_t x, uint32_t tag) {
  asm volatile("st.relaxed.gpu.global.b64 [%0], %1;" ::"l"(p), "l"(((uint64_t)tag << 32) | x) : "memory");
}
__device__ __forceinline__ uint4 ld_acquire4(const uint32_t* p) {
  uint4 v; asm volatile("ld.acquire.gpu.global.v4.u32 {%0, %1, %2, %3}, [%4];" : "=r"(v.x), "=r"(v.y), "=r"(v.z), "=r"(v.w) : "l"(p) : "memory"); return v;
}
__device__ __forceinline__ ulonglong2 ld_ll2(const ulonglong2* p) {
  ulonglong2 v; asm volatile("ld.relaxed.gpu.global.v2.b64 {%0, %1}, [%2];" : "=l"(v.x), "=l"(v.y) : "l"(p) : "memory"); return v;
}
__device__ __forceinline__ void st_ll2(ulonglong2* p, uint32_t x, uint32_t y, uint32_t tag) {
  asm volatile("st.relaxed.gpu.global.v2.b64 [%0], {%1, %2};" ::"l"(p), "l"(((uint64_t)tag << 32) | x), "l"(((uint64_t)tag << 32) | y) : "memory");
}
__device__ __forceinline__ void sts32(uint32_t a, uint32_t x) { asm volatile("st.shared.u32 [%0], %1;" ::"r"(a), "r"(x) : "memory"); }
__device__ __forceinline__ uint32_t lds32(uint32_t a) { uint32_t v; asm volatile("ld.shared.u32 %0, [%1];" : "=r"(v) : "r"(a) : "memory"); return v; }
__device__ __forceinline__ void sts64(uint32_t a, uint32_t x, uint32_t y) { asm volatile("st.shared.v2.u32 [%0], {%1, %2};" ::"r"(a), "r"(x), "r"(y) : "memory"); }
__device__ __forceinline__ void sts128(uint32_t a, uint4 v) { asm volatile("st.shared.v4.u32 [%0], {%1, %2, %3, %4};" ::"r"(a), "r"(v.x), "r"(v.y), "r"(v.z), "r"(v.w) : "memory"); }
__device__ __forceinline__ uint4 lds128(uint32_t a) { uint4 v; asm volatile("ld.shared.v4.u32 {%0, %1, %2, %3}, [%4];" : "=r"(v.x), "=r"(v.y), "=r"(v.z), "=r"(v.w) : "r"(a) : "memory"); return v; }
__device__ __forceinline__ uint2 lds64(uint32_t a) { uint2 v; asm volatile("ld.shared.v2.u32 {%0, %1}, [%2];" : "=r"(v.x), "=r"(v.y) : "r"(a) : "memory"); return v; }
__device__ __forceinline__ void fence_gpu() { asm volatile("fence.acq_rel.gpu;" ::: "memory"); }
__device__ __forceinline__ void cluster_arrive() { asm volatile("barrier.cluster.arrive.relaxed.aligned;" ::: "memory"); }
__device__ __forceinline__ void cluster_wait() { asm volatile("barrier.cluster.wait.aligned;" ::: "memory"); }
__device__ __forceinline__ uint32_t roff(int r) { return 160 * r + 16 * (r >> 2); }

template <int N> __device__ __forceinline__ void fence_regs(float* a) {
#pragma unroll
  for (int k = 0; k < N; k++) asm volatile("" : "+f"(a[k])::"memory");
}

__device__ __forceinline__ void wgmma_n48(float* d, uint64_t da, uint64_t db, int scale_d) {
  asm volatile("{\n.reg .pred p;\n"
    "setp.ne.b32 p, %26, 0;\n"
    "wgmma.mma_async.sync.aligned.m64n48k16.f32.bf16.bf16 "
    "{%0, %1, %2, %3, %4, %5, %6, %7, %8, %9, %10, %11, %12, %13, %14, %15, %16, %17, %18, %19, %20, %21, %22, %23}, %24, %25, p, 1, 1, 0, 1;\n}\n"
    : "+f"(d[0]), "+f"(d[1]), "+f"(d[2]), "+f"(d[3]), "+f"(d[4]), "+f"(d[5]), "+f"(d[6]), "+f"(d[7]),
      "+f"(d[8]), "+f"(d[9]), "+f"(d[10]), "+f"(d[11]), "+f"(d[12]), "+f"(d[13]), "+f"(d[14]), "+f"(d[15]),
      "+f"(d[16]), "+f"(d[17]), "+f"(d[18]), "+f"(d[19]), "+f"(d[20]), "+f"(d[21]), "+f"(d[22]), "+f"(d[23])
    : "l"(da), "l"(db), "r"(scale_d));
}
__device__ __forceinline__ void wgmma_n160(float* d, uint64_t da, uint64_t db, int scale_d) {
  asm volatile("{\n.reg .pred p;\n"
    "setp.ne.b32 p, %82, 0;\n"
    "wgmma.mma_async.sync.aligned.m64n160k16.f32.bf16.bf16 "
    "{%0, %1, %2, %3, %4, %5, %6, %7, %8, %9, %10, %11, %12, %13, %14, %15, %16, %17, %18, %19, %20, %21, %22, %23, %24, %25, %26, %27, %28, %29, %30, %31, %32, %33, %34, %35, %36, %37, %38, %39, %40, %41, %42, %43, %44, %45, %46, %47, %48, %49, %50, %51, %52, %53, %54, %55, %56, %57, %58, %59, %60, %61, %62, %63, %64, %65, %66, %67, %68, %69, %70, %71, %72, %73, %74, %75, %76, %77, %78, %79}, %80, %81, p, 1, 1, 0, 1;\n}\n"
    : "+f"(d[0]), "+f"(d[1]), "+f"(d[2]), "+f"(d[3]), "+f"(d[4]), "+f"(d[5]), "+f"(d[6]), "+f"(d[7]),
      "+f"(d[8]), "+f"(d[9]), "+f"(d[10]), "+f"(d[11]), "+f"(d[12]), "+f"(d[13]), "+f"(d[14]), "+f"(d[15]),
      "+f"(d[16]), "+f"(d[17]), "+f"(d[18]), "+f"(d[19]), "+f"(d[20]), "+f"(d[21]), "+f"(d[22]), "+f"(d[23]),
      "+f"(d[24]), "+f"(d[25]), "+f"(d[26]), "+f"(d[27]), "+f"(d[28]), "+f"(d[29]), "+f"(d[30]), "+f"(d[31]),
      "+f"(d[32]), "+f"(d[33]), "+f"(d[34]), "+f"(d[35]), "+f"(d[36]), "+f"(d[37]), "+f"(d[38]), "+f"(d[39]),
      "+f"(d[40]), "+f"(d[41]), "+f"(d[42]), "+f"(d[43]), "+f"(d[44]), "+f"(d[45]), "+f"(d[46]), "+f"(d[47]),
      "+f"(d[48]), "+f"(d[49]), "+f"(d[50]), "+f"(d[51]), "+f"(d[52]), "+f"(d[53]), "+f"(d[54]), "+f"(d[55]),
      "+f"(d[56]), "+f"(d[57]), "+f"(d[58]), "+f"(d[59]), "+f"(d[60]), "+f"(d[61]), "+f"(d[62]), "+f"(d[63]),
      "+f"(d[64]), "+f"(d[65]), "+f"(d[66]), "+f"(d[67]), "+f"(d[68]), "+f"(d[69]), "+f"(d[70]), "+f"(d[71]),
      "+f"(d[72]), "+f"(d[73]), "+f"(d[74]), "+f"(d[75]), "+f"(d[76]), "+f"(d[77]), "+f"(d[78]), "+f"(d[79])
    : "l"(da), "l"(db), "r"(scale_d));
}
__device__ __forceinline__ void wgmma_n192(float* d, uint64_t da, uint64_t db, int scale_d) {
  asm volatile("{\n.reg .pred p;\n"
    "setp.ne.b32 p, %98, 0;\n"
    "wgmma.mma_async.sync.aligned.m64n192k16.f32.bf16.bf16 "
    "{%0, %1, %2, %3, %4, %5, %6, %7, %8, %9, %10, %11, %12, %13, %14, %15, %16, %17, %18, %19, %20, %21, %22, %23, %24, %25, %26, %27, %28, %29, %30, %31, %32, %33, %34, %35, %36, %37, %38, %39, %40, %41, %42, %43, %44, %45, %46, %47, %48, %49, %50, %51, %52, %53, %54, %55, %56, %57, %58, %59, %60, %61, %62, %63, %64, %65, %66, %67, %68, %69, %70, %71, %72, %73, %74, %75, %76, %77, %78, %79, %80, %81, %82, %83, %84, %85, %86, %87, %88, %89, %90, %91, %92, %93, %94, %95}, %96, %97, p, 1, 1, 0, 1;\n}\n"
    : "+f"(d[0]), "+f"(d[1]), "+f"(d[2]), "+f"(d[3]), "+f"(d[4]), "+f"(d[5]), "+f"(d[6]), "+f"(d[7]),
      "+f"(d[8]), "+f"(d[9]), "+f"(d[10]), "+f"(d[11]), "+f"(d[12]), "+f"(d[13]), "+f"(d[14]), "+f"(d[15]),
      "+f"(d[16]), "+f"(d[17]), "+f"(d[18]), "+f"(d[19]), "+f"(d[20]), "+f"(d[21]), "+f"(d[22]), "+f"(d[23]),
      "+f"(d[24]), "+f"(d[25]), "+f"(d[26]), "+f"(d[27]), "+f"(d[28]), "+f"(d[29]), "+f"(d[30]), "+f"(d[31]),
      "+f"(d[32]), "+f"(d[33]), "+f"(d[34]), "+f"(d[35]), "+f"(d[36]), "+f"(d[37]), "+f"(d[38]), "+f"(d[39]),
      "+f"(d[40]), "+f"(d[41]), "+f"(d[42]), "+f"(d[43]), "+f"(d[44]), "+f"(d[45]), "+f"(d[46]), "+f"(d[47]),
      "+f"(d[48]), "+f"(d[49]), "+f"(d[50]), "+f"(d[51]), "+f"(d[52]), "+f"(d[53]), "+f"(d[54]), "+f"(d[55]),
      "+f"(d[56]), "+f"(d[57]), "+f"(d[58]), "+f"(d[59]), "+f"(d[60]), "+f"(d[61]), "+f"(d[62]), "+f"(d[63]),
      "+f"(d[64]), "+f"(d[65]), "+f"(d[66]), "+f"(d[67]), "+f"(d[68]), "+f"(d[69]), "+f"(d[70]), "+f"(d[71]),
      "+f"(d[72]), "+f"(d[73]), "+f"(d[74]), "+f"(d[75]), "+f"(d[76]), "+f"(d[77]), "+f"(d[78]), "+f"(d[79]),
      "+f"(d[80]), "+f"(d[81]), "+f"(d[82]), "+f"(d[83]), "+f"(d[84]), "+f"(d[85]), "+f"(d[86]), "+f"(d[87]),
      "+f"(d[88]), "+f"(d[89]), "+f"(d[90]), "+f"(d[91]), "+f"(d[92]), "+f"(d[93]), "+f"(d[94]), "+f"(d[95])
    : "l"(da), "l"(db), "r"(scale_d));
}
__device__ __forceinline__ void wgmma_n216(float* d, uint64_t da, uint64_t db, int scale_d) {
  asm volatile("{\n.reg .pred p;\n"
    "setp.ne.b32 p, %110, 0;\n"
    "wgmma.mma_async.sync.aligned.m64n216k16.f32.bf16.bf16 "
    "{%0, %1, %2, %3, %4, %5, %6, %7, %8, %9, %10, %11, %12, %13, %14, %15, %16, %17, %18, %19, %20, %21, %22, %23, %24, %25, %26, %27, %28, %29, %30, %31, %32, %33, %34, %35, %36, %37, %38, %39, %40, %41, %42, %43, %44, %45, %46, %47, %48, %49, %50, %51, %52, %53, %54, %55, %56, %57, %58, %59, %60, %61, %62, %63, %64, %65, %66, %67, %68, %69, %70, %71, %72, %73, %74, %75, %76, %77, %78, %79, %80, %81, %82, %83, %84, %85, %86, %87, %88, %89, %90, %91, %92, %93, %94, %95, %96, %97, %98, %99, %100, %101, %102, %103, %104, %105, %106, %107}, %108, %109, p, 1, 1, 0, 1;\n}\n"
    : "+f"(d[0]), "+f"(d[1]), "+f"(d[2]), "+f"(d[3]), "+f"(d[4]), "+f"(d[5]), "+f"(d[6]), "+f"(d[7]),
      "+f"(d[8]), "+f"(d[9]), "+f"(d[10]), "+f"(d[11]), "+f"(d[12]), "+f"(d[13]), "+f"(d[14]), "+f"(d[15]),
      "+f"(d[16]), "+f"(d[17]), "+f"(d[18]), "+f"(d[19]), "+f"(d[20]), "+f"(d[21]), "+f"(d[22]), "+f"(d[23]),
      "+f"(d[24]), "+f"(d[25]), "+f"(d[26]), "+f"(d[27]), "+f"(d[28]), "+f"(d[29]), "+f"(d[30]), "+f"(d[31]),
      "+f"(d[32]), "+f"(d[33]), "+f"(d[34]), "+f"(d[35]), "+f"(d[36]), "+f"(d[37]), "+f"(d[38]), "+f"(d[39]),
      "+f"(d[40]), "+f"(d[41]), "+f"(d[42]), "+f"(d[43]), "+f"(d[44]), "+f"(d[45]), "+f"(d[46]), "+f"(d[47]),
      "+f"(d[48]), "+f"(d[49]), "+f"(d[50]), "+f"(d[51]), "+f"(d[52]), "+f"(d[53]), "+f"(d[54]), "+f"(d[55]),
      "+f"(d[56]), "+f"(d[57]), "+f"(d[58]), "+f"(d[59]), "+f"(d[60]), "+f"(d[61]), "+f"(d[62]), "+f"(d[63]),
      "+f"(d[64]), "+f"(d[65]), "+f"(d[66]), "+f"(d[67]), "+f"(d[68]), "+f"(d[69]), "+f"(d[70]), "+f"(d[71]),
      "+f"(d[72]), "+f"(d[73]), "+f"(d[74]), "+f"(d[75]), "+f"(d[76]), "+f"(d[77]), "+f"(d[78]), "+f"(d[79]),
      "+f"(d[80]), "+f"(d[81]), "+f"(d[82]), "+f"(d[83]), "+f"(d[84]), "+f"(d[85]), "+f"(d[86]), "+f"(d[87]),
      "+f"(d[88]), "+f"(d[89]), "+f"(d[90]), "+f"(d[91]), "+f"(d[92]), "+f"(d[93]), "+f"(d[94]), "+f"(d[95]),
      "+f"(d[96]), "+f"(d[97]), "+f"(d[98]), "+f"(d[99]), "+f"(d[100]), "+f"(d[101]), "+f"(d[102]), "+f"(d[103]),
      "+f"(d[104]), "+f"(d[105]), "+f"(d[106]), "+f"(d[107])
    : "l"(da), "l"(db), "r"(scale_d));
}

__device__ __forceinline__ void softmax_head(const float (*s)[4], bool gt0, bool gt1, bool first, float glo, float ghi, uint32_t& plo, uint32_t& phi) {
  constexpr float C = 0.22360679774997896f * 1.4426950408889634f;
  float v0 = gt0 ? s[0][0] : s[1][0], v1 = gt1 ? s[0][1] : s[1][1];
  const float v2 = gt0 ? s[1][2] : s[2][2], v3 = gt1 ? s[1][3] : s[2][3];
  if (first) {
    if (gt0) v0 = -1e9f;
    if (gt1) v1 = -1e9f;
  }
  float ml = fmaxf(v0, v1), mh = fmaxf(v2, v3);
  ml = fmaxf(ml, __shfl_xor_sync(0xffffffffu, ml, 1)); mh = fmaxf(mh, __shfl_xor_sync(0xffffffffu, mh, 1));
  ml = fmaxf(ml, __shfl_xor_sync(0xffffffffu, ml, 2)); mh = fmaxf(mh, __shfl_xor_sync(0xffffffffu, mh, 2));
  ml *= C; mh *= C;
  const float e0 = ex2(fmaf(v0, C, -ml)), e1 = ex2(fmaf(v1, C, -ml)), e2 = ex2(fmaf(v2, C, -mh)), e3 = ex2(fmaf(v3, C, -mh));
  float sl = e0 + e1, sh = e2 + e3;
  sl += __shfl_xor_sync(0xffffffffu, sl, 1); sh += __shfl_xor_sync(0xffffffffu, sh, 1);
  sl += __shfl_xor_sync(0xffffffffu, sl, 2); sh += __shfl_xor_sync(0xffffffffu, sh, 2);
  const float fl = glo * rcp(sl), fh = ghi * rcp(sh);
  plo = pack_bf16(e0 * fl, e1 * fl);
  phi = pack_bf16(e2 * fh, e3 * fh);
}
__device__ __forceinline__ void pv_head(float (*o)[4], uint32_t plo, uint32_t phi, uint32_t M, const uint32_t (*v)[5], int c0) {
  const uint32_t a0 = plo & M, a2 = plo & ~M, a3 = phi & M, a5 = phi & ~M;
#pragma unroll
  for (int c = 0; c < 3; c++) mma16z(o[c], a0, 0u, a2, a3, v[0][c0 + c], v[1][c0 + c]);
#pragma unroll
  for (int c = 0; c < 3; c++) mma8(o[c], 0u, a5, v[2][c0 + c]);
}
__device__ __forceinline__ void attention(uint32_t* q, uint32_t kplane, int lane, bool first, float glo, float ghi) {
  const int rho = lane >> 2, qd = lane & 3, m = lane >> 3, row = lane & 7;
  const bool gt0 = 2 * qd > rho, gt1 = 2 * qd + 1 > rho;
  const uint32_t M = (gt0 ? 0xffffu : 0u) | (gt1 ? 0xffff0000u : 0u);
  const uint32_t mA = qd < 2 ? 0xffffffffu : 0u;
  const uint32_t ra = kplane + 160 * row + 16 * (row >> 2);
  uint32_t aA = ra + 16 * m, aB = ra + 1312 * (m < 2 ? m : 2) + 64;
#pragma unroll 1
  for (int pr = 0; pr < 2; pr++) {
    uint32_t plo0, phi0, plo1, phi1;
    {
      uint32_t k[3][5], kb[4];
#pragma unroll
      for (int t = 0; t < 3; t++) ldsm4(k[t], aA + 1312 * t);
      ldsm4(kb, aB);
#pragma unroll
      for (int t = 0; t < 3; t++) k[t][4] = kb[t];
      float s0[3][4], s1[3][4];
#pragma unroll
      for (int t = 0; t < 3; t++) {
        mma16z(s0[t], q[0], q[1], q[2], q[3], k[t][0], k[t][1]);
        mma16z(s1[t], q[6], q[7], q[8], q[9], k[t][3], k[t][4]);
      }
#pragma unroll
      for (int t = 0; t < 3; t++) {
        mma8(s0[t], q[4] & mA, q[5] & mA, k[t][2]);
        mma8(s1[t], q[4] & ~mA, q[5] & ~mA, k[t][2]);
      }
      softmax_head(s0, gt0, gt1, first, glo, ghi, plo0, phi0);
      softmax_head(s1, gt0, gt1, first, glo, ghi, plo1, phi1);
    }
    uint32_t v[3][5], vb[4];
#pragma unroll
    for (int t = 0; t < 3; t++) ldsm4t(v[t], aA + 2 * PLANE + 1312 * t);
    ldsm4t(vb, aB + 2 * PLANE);
#pragma unroll
    for (int t = 0; t < 3; t++) v[t][4] = vb[t];
    float o0[3][4], o1[3][4];
    pv_head(o0, plo0, phi0, M, v, 0);
    pv_head(o1, plo1, phi1, M, v, 2);
#pragma unroll
    for (int c = 0; c < 10; c++) q[c] = q[10 + c];
    uint32_t* oo = q + 10;
    oo[0] = pack_bf16(o0[0][0], o0[0][1]); oo[1] = pack_bf16(o0[0][2], o0[0][3]);
    oo[2] = pack_bf16(o0[1][0], o0[1][1]); oo[3] = pack_bf16(o0[1][2], o0[1][3]);
    oo[4] = qd < 2 ? pack_bf16(o0[2][0], o0[2][1]) : pack_bf16(o1[0][0], o1[0][1]);
    oo[5] = qd < 2 ? pack_bf16(o0[2][2], o0[2][3]) : pack_bf16(o1[0][2], o1[0][3]);
    oo[6] = pack_bf16(o1[1][0], o1[1][1]); oo[7] = pack_bf16(o1[1][2], o1[1][3]);
    oo[8] = pack_bf16(o1[2][0], o1[2][1]); oo[9] = pack_bf16(o1[2][2], o1[2][3]);
    aA += 80; aB += 80;
  }
}

__device__ __forceinline__ uint32_t read_tag() { return (*reinterpret_cast<volatile uint32_t*>(&g_done) >> 7) + 1; }
__device__ __forceinline__ uint32_t clock32() { uint32_t c; asm volatile("mov.u32 %0, %%clock;" : "=r"(c)); return c; }

struct Ring {
  int pa;
  int ua;
  int sw;
  uint32_t pw;
  uint32_t spin;
};

template <int PH, class F>
__device__ __forceinline__ void mma_loop(float* acc, Ring& rg, uint32_t bar, uint32_t rel, uint32_t dlo_a, uint32_t dlo_b, int lane, int trbase, F mid) {
  int prevw = -1, preva = -1;
#pragma unroll 1
  for (int n = 0; n < (PH == 2 ? N_P3 : 20); n++) {
    const int h = PH == 2 ? ((n - (n > 26)) & 1) : (n & 1);
    if (h == 0 && (PH != 1 || n >= 8)) { mbar_wait(bar + 8 * (B_AF + rg.pa), (rg.ua >> 2) & 1, rg.spin); rg.ua++; }
    mbar_wait(bar + 8 * (B_WF + rg.sw), rg.pw, rg.spin);
    const uint64_t da = ((uint64_t)((1024u >> 4) | (1u << 30)) << 32) | (dlo_a + rg.pa * (PAGE >> 4) + h * 4);
    const uint64_t db = ((uint64_t)((1024u >> 4) | (1u << 30)) << 32) | (dlo_b + rg.sw * (PAGE >> 4));
    const int sc = n != 0;
    wg_fence();
    if (PH == 0) { wgmma_n216(acc, da, db, sc); wgmma_n216(acc, da + 2, db + 128, 1); }
    if (PH == 1) {
      const uint64_t dn = ((uint64_t)((256u >> 4) | (3u << 30)) << 32) | (((dlo_b + 768u) & 0xffffu) + rg.sw * (PAGE >> 4)) | ((1024u >> 4) << 16);
      wgmma_n192(acc, da, db, sc); wgmma_n48(acc + 96, da, dn, sc);
      wgmma_n192(acc, da + 2, db + 128, 1); wgmma_n48(acc + 96, da + 2, dn + 32, 1);
    }
    if (PH == 2) { wgmma_n160(acc, da, db, sc); wgmma_n160(acc, da + 2, db + 128, 1); }
    wg_commit();
    if (prevw >= 0) {
      wg_wait<1>();
      if (lane < 2) mbar_arrive_remote(rel + 8 * prevw);
      if (lane == 2 && preva >= 0) mbar_arrive(bar + 8 * (B_AE + preva));
    }
    prevw = (PH == 2 && n >= N_P3 - NW) ? -1 : rg.sw;
    preva = -1;
    if (h == 1 || (PH == 2 && n == 26)) {
      if (PH != 0 || n < 12) preva = rg.pa;
      rg.pa = (rg.pa + 1) & 3;
    }
    if (++rg.sw == NW) { rg.sw = 0; rg.pw ^= 1; }
    if (PH == 2 && n == ATT_POS - 1) { wg_wait<0>(); mid(); }
  }
  wg_wait<0>();
  fence_regs<PH == 0 ? 108 : (PH == 1 ? 120 : 80)>(acc);
  if (PH != 2) {
    if (lane < 2) mbar_arrive_remote(rel + 8 * prevw);
    if (lane == 2 && preva >= 0) mbar_arrive(bar + 8 * (B_AE + preva));
  }
}

__global__ void __cluster_dims__(2, 1, 1) __launch_bounds__(NTHREADS, 1)
fused_kernel(const __nv_bfloat16* __restrict__ px, const __nv_bfloat16* __restrict__ pw1, const __nv_bfloat16* __restrict__ pb1, const __nv_bfloat16* __restrict__ pgate,
             __nv_bfloat16* __restrict__ pout, const __nv_bfloat16* __restrict__ pb2, const __grid_constant__ Params p) {
  extern __shared__ __align__(1024) uint8_t smem_raw[];
  const uint32_t sb = smem_u32(smem_raw);
  const uint32_t bar = sb + BAR_OFF;
  const int tid = threadIdx.x;
  const int warp = __shfl_sync(0xffffffffu, tid >> 5, 0);
  const int lane = tid & 31;
#define TC(v) do {} while (0)
  const int r = blockIdx.x & 1;
  const int c_ = blockIdx.x >> 1;
  const int L = c_ < 4 ? 4 + c_ : (c_ < 36 ? ((c_ - 4) & 7) * 8 + ((c_ - 4) >> 3) : (1 + (c_ - 36) % 7) * 8 + 4 + (c_ - 36) / 7);
  const int G = L >> 3, pp = L & 7;
  const int i = 4 * (G >> 1) + 2 * (pp >> 2) + r;
  const int j = 4 * (G & 1) + (pp & 3);
  const int t = pp & 3, kh = G & 1;
  const uint32_t cs = i * 8 + j;
  uint32_t spin = 0;

  constexpr int N_EARLY = 2;
  const uint8_t* pf = nullptr;
  uint32_t pfs = 0;
  if (warp == 3) {
    pf = lane < 16 ? reinterpret_cast<const uint8_t*>(px) + (16 * cs + lane) * (DM * 2) : reinterpret_cast<const uint8_t*>(pw1) + (cs * 1728 + (lane - 16) * 128);
    pfs = lane < 16 ? 128u : 64u * FF * 2u;
    if (lane < 30) { prefetch_l2(pf); prefetch_l2(pf + pfs); }
  }
  if (warp < 2) {
    if (elect_one()) {
      if (warp == 0) {
        mbar_init(bar + 8 * B_AF, 1);
#pragma unroll
        for (int b = 0; b < N_EARLY; b++) mbar_init(bar + 8 * (B_WF + b), 1);
        fence_async_smem();
        TC(tc1);
        mbar_expect_tx(bar + 8 * B_AF, PAGE);
        tma_4d(sb, &p.a[0], 0, 0, 0, 4 * i, bar + 8 * B_AF);
#pragma unroll
        for (int n = 0; n < N_EARLY; n++) {
          const uint32_t fb = bar + 8 * (B_WF + n), dst = sb + WB + n * PAGE;
          mbar_expect_tx(fb, BYTES_W1);
          tma_4d(dst, &p.w[0], 0, n * 32, 0, j, fb);
          tma_4d(dst + 12288, &p.w[1], 0, n * 32, 0, j, fb);
        }
        TC(tc3);
      } else {
#pragma unroll
        for (int b = 1; b < B_NBAR; b++) {
          if (b >= B_WF && b < B_WF + N_EARLY) continue;
          mbar_init(bar + 8 * b, b >= B_WE && b < B_WE + NW ? 16 : ((b >= B_AE && b < B_AE + NA) || b == B_HDONE || b == B_ODONE ? 8 : (b == B_GREADY || b == B_KV ? 2 : 1)));
        }
      }
      asm volatile("fence.mbarrier_init.release.cluster;" ::: "memory");
      fence_async_smem();
    }
    __syncwarp();
  }
  TC(tc2);
  cluster_arrive();
  TC(tc5);
  if (warp < 4) {
    asm volatile("{\n.reg .pred p;\nsetp.ne.u32 p, %0, 0;\n@p trap;\n}" ::"r"(sb & 1023));
    if (warp != 1) cluster_wait();
    if (warp < 1) {
      if (elect_one()) {
        int sl = N_EARLY; uint32_t ph = 1;
        uint32_t dst0 = sb + WB + (r == 0 ? 0u : 12288u), bytes = BYTES_W1;
        const CUtensorMap* tm = &p.w[r];
        int c3 = j, kn = 32 * N_EARLY, cnt = N_H - N_EARLY;
#pragma unroll 1
        for (int s = 0; s < 5; s++) {
          if (s == 1) { bytes = 15360; kn = 384; cnt = N_QKV; }
          if (s == 2) { c3 = t; dst0 -= 4096 * r; bytes = BYTES_W2; cnt = 24; }
          if (s == 3) { kn = 1536 + 96 * kh; cnt = 3; }
          if (s == 4) { kn = 320 * kh; cnt = 10; }
          if (s != 0 && s != 3) tm += 2;
#pragma unroll 1
          for (int m = 0; m < cnt; m++) {
            int k = kn;
            kn += 32;
            if (s == 1 && kn == DM) kn = 0;
            if (s == 2) k = 768 * kh + 192 * ((t + (m >> 1)) & 3) + 64 * (m >> 3) + 32 * (m & 1);
            mbar_wait(bar + 8 * (B_WE + sl), ph, spin);
            mbar_expect_tx(bar + 8 * (B_WF + sl), bytes);
            tma_4d_mc(dst0 + sl * PAGE, tm, 0, k, 0, c3, bar + 8 * (B_WF + sl));
            if (++sl == NW) { sl = 0; ph ^= 1; }
          }
        }
      }
    } else if (warp < 2) {
      if (elect_one()) {
        const uint32_t* fl = g_flag + i * 32;
#pragma unroll 1
        for (int u = 1; u < 35; u++) {
          if (u == 4) {
#pragma unroll 1
            for (int m = 2; m < 15; m++) prefetch_tmap(reinterpret_cast<const CUtensorMap*>(&p) + m);
          }
          if (u == 6) {
            l2_prefetch(reinterpret_cast<const uint8_t*>(p.pwqkv) + cs * 19200u, 19200);
            l2_prefetch(reinterpret_cast<const uint8_t*>(p.pw2) + cs * 17280u, 17280);
            l2_prefetch(reinterpret_cast<const uint8_t*>(p.pwo) + cs * 6400u, 6400);
          }
          int k = 64 * (u < 10 ? u : u - 10), need = 0, fo = kh;
          const CUtensorMap* tm = &p.a[0];
          if (u >= 16) {
            const int m = u - 16;
            tm = &p.a[1];
            k = 768 * kh + 192 * ((t + m) & 3) + 64 * (m >> 2);
            if ((m & 3) == 0) need = (m >> 2) + 1;
            if (u >= 28) k = 1536 + 96 * kh + 64 * (u - 28);
            if (u == 29) { need = 1; fo = 1 - kh; }
            if (u >= 30) { tm = &p.a[2]; k = 320 * kh + 64 * (u - 30); need = u == 30 ? 4 : 0; fo = 2 + kh; }
          }
          if (need) {
            const uint32_t base = 4 * (read_tag() - 1);
            uint4 v;
            do { v = ld_acquire4(fl + 4 * fo); }
            while (((int)(v.x - base) < need || (int)(v.y - base) < need || (int)(v.z - base) < need || (int)(v.w - base) < need) && ++spin < SPIN_MAX);
            fence_async_glob();
            TR(u == 29 ? 38 : (u == 30 ? 39 : 39 + need));
          }
          const int sl = u & 3;
          mbar_wait(bar + 8 * (B_AE + sl), ((u >> 2) & 1) ^ 1, spin);
          mbar_expect_tx(bar + 8 * (B_AF + sl), PAGE);
          tma_4d(sb + sl * PAGE, tm, k, 0, 0, 4 * i, bar + 8 * (B_AF + sl));
          TRW(150 + u);
        }
      }
    } else {
      const int w2 = warp - 2;
      const uint32_t tag = read_tag();
      {
        mbar_wait(bar + 8 * B_AF, 0, spin);
        if (w2 == 1 && lane < 30) {
#pragma unroll 1
          for (int m = 2; m < 10; m++) prefetch_l2(pf + (size_t)m * pfs);
        }
        if (w2 == 0 && elect_one()) {
          mbar_expect_tx(bar + 8 * B_XG, 17 * DM * 2);
          bulk_load(sb + R0, reinterpret_cast<const uint8_t*>(px) + cs * (16u * DM * 2u), 16 * DM * 2, bar + 8 * B_XG);
          bulk_load(sb + R0 + 16 * DM * 2, pgate, DM * 2, bar + 8 * B_XG);
        }
        {
          const int nw = w2 == 0 ? 24 : 16;
          const __nv_bfloat16* bp = w2 == 0 ? pb1 + (lane < nw ? 192 * j : 1536 + 24 * j - 192) : pb2 + (lane < nw ? 128 * t : 512 + 32 * t - 128);
          if (lane < (w2 == 0 ? 27 : 20)) sts128(sb + BIAS_OFF + 448 * w2 + 16 * lane, __ldg(reinterpret_cast<const uint4*>(bp) + lane));
        }
        mbar_wait(bar + 8 * B_XG, 0, spin);
        float s0 = 0.f, s1 = 0.f;
        const uint32_t xa = sb + R0 + (8 * w2 + (lane >> 2)) * (DM * 2) + 16 * (lane & 3), wa = sb + R0 + 16 * DM * 2 + 16 * (lane & 3);
#pragma unroll 2
        for (int c = 0; c < 20; c++) {
          const uint4 x = lds128(xa + 64 * c), w = lds128(wa + 64 * c);
          const uint32_t a = mul_bf16x2(x.x, w.x), b = mul_bf16x2(x.y, w.y), d = mul_bf16x2(x.z, w.z), e = mul_bf16x2(x.w, w.w);
          s0 += (bf_lo(a) + bf_hi(a)) + (bf_lo(b) + bf_hi(b));
          s1 += (bf_lo(d) + bf_hi(d)) + (bf_lo(e) + bf_hi(e));
        }
        s0 += s1;
        s0 += __shfl_xor_sync(0xffffffffu, s0, 1);
        s0 += __shfl_xor_sync(0xffffffffu, s0, 2);
        if ((lane & 3) == 0) {
          const float z = __bfloat162float(__float2bfloat16(s0));
          const float g = rcp(1.f + ex2(z * -1.4426950408889634f));
          st_ll(&g_gateLL[16 * cs + 8 * w2 + (lane >> 2)], (uint32_t)__bfloat16_as_ushort(__float2bfloat16(g)), tag);
        }
        if (lane == 0 && warp == 2) TR(11);
        {
          const int row = 64 * w2 + 2 * lane;
          ulonglong2 v;
          do { v = ld_ll2(reinterpret_cast<const ulonglong2*>(g_gateLL + (128 * i + row))); }
          while (((uint32_t)(v.x >> 32) != tag || (uint32_t)(v.y >> 32) != tag) && ++spin < SPIN_MAX);
          sts32(sb + G_OFF + 2 * row, (uint32_t)v.x | ((uint32_t)v.y << 16));
        }
        __syncwarp();
        if (lane == 0) { mbar_arrive(bar + 8 * B_GREADY); if (warp == 2) TR(2); }
        {
          uint4* ow = reinterpret_cast<uint4*>(reinterpret_cast<uint8_t*>(pout) +
                                               (uint32_t)((128 * i + 64 * kh + 32 * w2) * (DM * 2) + (lane < 16 ? 256 * t : 1024 - 256 + 64 * t) + 16 * lane));
          if (lane < 20) {
#pragma unroll 1
            for (int it = 0; it < 32; it++) ow[it * (DM / 8)] = make_uint4(0u, 0u, 0u, 0u);
          }
        }
        if (lane == 0 && warp == 2) TR(13);
        asm volatile("bar.sync 2, 64;" ::: "memory");
      }
      if (w2 == 0) {
        if (elect_one()) {
          uint32_t* flag = g_flag + i * 32 + j;
          fence_gpu();
          mbar_wait(bar + 8 * B_HDONE, 0, spin);
          const uint32_t t0 = clock32();
#pragma unroll 1
          for (int q = 0; q < 12; q++) {
            const int pc = q >> 2;
            while (clock32() - t0 < H_PACE * (uint32_t)q) {}
            tma_store_4d(&p.hst, sb + R0 + q * 4096, 192 * j + 64 * pc, 0, 0, 4 * i + (q & 3));
            asm volatile("cp.async.bulk.commit_group;" ::: "memory");
            if ((q & 3) == 0 && q > 0) {
              asm volatile("cp.async.bulk.wait_group 1;" ::: "memory");
              st_flag(flag, 4 * (tag - 1) + pc);
              TR(44 + pc);
            }
          }
          asm volatile("cp.async.bulk.wait_group.read 0;" ::: "memory");
          mbar_arrive(bar + 8 * B_HFREE);
          asm volatile("cp.async.bulk.wait_group 0;" ::: "memory");
          st_flag(flag, 4 * (tag - 1) + 3);
          TR(47);
          fence_gpu();
          st_flag(flag, 4 * tag);
          TR(48);
          mbar_wait(bar + 8 * B_ODONE, 0, spin);
          tma_store_4d(&p.ost, sb + R0, 80 * j, 0, 0, 4 * i);
          asm volatile("cp.async.bulk.commit_group;" ::: "memory");
          asm volatile("cp.async.bulk.wait_group 0;" ::: "memory");
          TR(49);
          st_flag(flag + 8, 4 * tag);
          TR(50);
        }
      } else if (elect_one()) {
        constexpr uint32_t HB = 8 * 160 + 32;
        mbar_wait(bar + 8 * B_KV, 0, spin);
#pragma unroll 1
        for (uint32_t b = 0; b < 4; b++) bulk_store(g_halo + (cs * 4 + b) * HB, sb + R0 + roff(64) + b * PLANE, HB);
        asm volatile("cp.async.bulk.commit_group;" ::: "memory");
        asm volatile("cp.async.bulk.wait_group 0;" ::: "memory");
        st_flag(g_flag + i * 32 + 16 + j, tag);
        TR(53);
        const uint32_t src = i > 0 ? cs - 8 : cs;
        while (ld_acquire(g_flag + (src >> 3) * 32 + 16 + j) != tag && ++spin < SPIN_MAX) {}
        fence_async_glob();
        mbar_wait(bar + 8 * B_HFREE, 0, spin);
        TR(51);
        mbar_expect_tx(bar + 8 * B_HALO, 4 * HB);
#pragma unroll 1
        for (uint32_t b = 0; b < 4; b++) bulk_load(sb + R0 + b * PLANE, g_halo + (src * 4 + b) * HB, HB, bar + 8 * B_HALO);
        TR(54);
      }
    }
  } else {
    const int w8 = warp - 4, cw = w8 >> 2;
    const uint32_t dlo_a = (((sb + cw * 8192) & 0x3FFFF) >> 4) | (1u << 16);
    const uint32_t dlo_b = (((sb + WB) & 0x3FFFF) >> 4) | ((4096u >> 4) << 16);
    const int trb = 200 + 100 * cw;
    Ring rg = {0, 0, 0, 0u, 0u};
    const int srow = (lane & 7) + 8 * ((lane >> 3) & 1);
    const int prow = 32 * (w8 >> 1) + 2 * (lane >> 2) + (w8 & 1);
    const uint32_t rel = mapa(bar + 8 * B_WE, lane & 1 ? 1 - r : r);
    const uint32_t bias = sb + BIAS_OFF + 16 * (lane >> 3);
    auto nomid = []() {};
    TC(tc1);
    cluster_wait();
    TC(tc2);
    uint32_t om0, om1;
    {
      float acc[108];
      mma_loop<0>(acc, rg, bar, rel, dlo_a, dlo_b, lane, trb, nomid);
      if ((w8 & 3) == 0 && lane == 0) TR(400 + 20 * cw);
      mbar_wait(bar + 8 * B_GREADY, 0, rg.spin);
      const float g0 = __uint_as_float(lds16(sb + G_OFF + 2 * prow) << 16), g1 = __uint_as_float(lds16(sb + G_OFF + 2 * (prow + 16)) << 16);
      om0 = pack_bf16(1.f - g0, 1.f - g0); om1 = pack_bf16(1.f - g1, 1.f - g1);
      const int sr = 16 * w8 + srow;
      const uint32_t sa = sb + R0 + sr * 128, x4 = (uint32_t)(((lane >> 4) ^ (sr & 7)) << 4);
      uint32_t* hn = reinterpret_cast<uint32_t*>(g_H) + (uint32_t)((128 * i + 16 * w8 + (lane >> 2)) * (FF / 2) + 768 + 12 * j + (lane & 3));
#pragma unroll
      for (int g32 = 0; g32 < 7; g32++) {
        uint32_t b[4], v[8];
        ldsm4(b, bias + 64 * g32);
#pragma unroll
        for (int e = 0; e < (g32 < 6 ? 8 : 6); e++) {
          const uint32_t rl = add_relu_bf16x2(pack_bf16(acc[16 * g32 + 2 * e], acc[16 * g32 + 2 * e + 1]), b[e >> 1]);
          v[e] = mul_bf16x2(mul_bf16x2(rl, rl), (e & 1) ? om1 : om0);
        }
        if (g32 < 6) {
#pragma unroll
          for (int e = 0; e < 2; e++) {
            const int g8 = 4 * g32 + 2 * e;
            stmatrix_x4(sa + (g8 >> 3) * 16384 + ((uint32_t)((g8 & 7) << 4) ^ x4), v[4 * e], v[4 * e + 1], v[4 * e + 2], v[4 * e + 3]);
          }
        } else {
#pragma unroll
          for (int e = 0; e < 6; e++) hn[(e & 1) * 8 * (FF / 2) + 4 * (e >> 1)] = v[e];
        }
      }
      fence_async_smem();
      __syncwarp();
      if (lane == 0) mbar_arrive(bar + 8 * B_HDONE);
      if ((w8 & 3) == 0 && lane == 0) TR(400 + 20 * cw + 1);
    }
    uint32_t q[20];
    const uint32_t kplane = sb + R0 + (w8 & 1) * PLANE + roff(16 * (w8 >> 1));
    {
      float acc[120];
      mma_loop<1>(acc, rg, bar, rel, dlo_a, dlo_b, lane, trb + N_H, nomid);
      if ((w8 & 3) == 0 && lane == 0) TR(400 + 20 * cw + 2);
      mbar_wait(bar + 8 * B_HFREE, 0, rg.spin);
      const uint32_t ka = kplane + roff(8 + srow) + (lane >> 4) * 16;
#pragma unroll
      for (int X = 0; X < 2; X++)
#pragma unroll
        for (int c = 0; c < 5; c++) {
          const int g8 = c < 4 ? 8 + 8 * X + 2 * c : 26 + 2 * X;
          stmatrix_x4(ka + X * 2 * PLANE + c * 32, pack_bf16(acc[4 * g8], acc[4 * g8 + 1]), pack_bf16(acc[4 * g8 + 2], acc[4 * g8 + 3]),
                      pack_bf16(acc[4 * g8 + 4], acc[4 * g8 + 5]), pack_bf16(acc[4 * g8 + 6], acc[4 * g8 + 7]));
        }
      if (w8 >= 6) {
        fence_async_smem();
        __syncwarp();
        if (lane == 0) mbar_arrive(bar + 8 * B_KV);
      }
#pragma unroll
      for (int c = 0; c < 10; c++) {
        const int g8 = c < 8 ? c : 16 + c;
        q[2 * c] = pack_bf16(acc[4 * g8], acc[4 * g8 + 1]); q[2 * c + 1] = pack_bf16(acc[4 * g8 + 2], acc[4 * g8 + 3]);
      }
      if ((w8 & 3) == 0 && lane == 0) TR(400 + 20 * cw + 3);
    }
    float acc[80];
    mma_loop<2>(acc, rg, bar, rel, dlo_a, dlo_b, lane, trb + N_H + N_QKV, [&]() {
      if ((w8 & 3) == 0 && lane == 0) TR(400 + 20 * cw + 4);
      mbar_wait(bar + 8 * B_HALO, 0, rg.spin);
      asm volatile("bar.sync 1, 256;" ::: "memory");
      if ((w8 & 3) == 0 && lane == 0) TR(400 + 20 * cw + 5);
      const float g0 = __uint_as_float(lds16(sb + G_OFF + 2 * prow) << 16), g1 = __uint_as_float(lds16(sb + G_OFF + 2 * (prow + 16)) << 16);
      attention(q, kplane, lane, i == 0 && w8 < 2, g0, g1);
      asm volatile("bar.sync 1, 256;" ::: "memory");
      const uint32_t oa = sb + R0 + (16 * w8 + srow) * 160 + (lane >> 4) * 16;
#pragma unroll
      for (int c = 0; c < 5; c++) stmatrix_x4(oa + c * 32, q[4 * c], q[4 * c + 1], q[4 * c + 2], q[4 * c + 3]);
      fence_async_smem();
      __syncwarp();
      if (lane == 0) mbar_arrive(bar + 8 * B_ODONE);
      if ((w8 & 3) == 0 && lane == 0) TR(400 + 20 * cw + 6);
    });
    if ((w8 & 3) == 0 && lane == 0) TR(400 + 20 * cw + 7);
    {
      if (kh != 0) { om0 = 0; om1 = 0; }
      const uint32_t st = sb + R0 + w8 * 5120;
      const uint32_t sa = st + srow * 128, x4 = (uint32_t)(((lane >> 4) ^ (srow & 7)) << 4);
      const uint32_t sn = st + 4096 + srow * 64, xn = (uint32_t)(((lane >> 4) ^ ((srow >> 1) & 3)) << 4);
#pragma unroll
      for (int g32 = 0; g32 < 5; g32++) {
        uint32_t b[4], v[8];
        ldsm4(b, bias + 448 + 64 * g32);
#pragma unroll
        for (int e = 0; e < 8; e++) v[e] = fma_bf16x2((e & 1) ? om1 : om0, b[e >> 1], pack_bf16(acc[16 * g32 + 2 * e], acc[16 * g32 + 2 * e + 1]));
#pragma unroll
        for (int e = 0; e < 2; e++) {
          const int g8 = 4 * g32 + 2 * e;
          stmatrix_x4(g8 < 16 ? sa + (g8 >> 3) * 2048 + ((uint32_t)((g8 & 7) << 4) ^ x4) : sn + ((uint32_t)((g8 & 3) << 4) ^ xn), v[4 * e], v[4 * e + 1], v[4 * e + 2], v[4 * e + 3]);
        }
      }
      fence_async_smem();
      fence_async_glob();
      __syncwarp();
      if (elect_one()) {
        const int c2 = w8 & 1, c3 = 4 * i + (w8 >> 1);
        tma_reduce_4d(&p.outw, st, 128 * t, c2, c3);
        tma_reduce_4d(&p.outw, st + 2048, 128 * t + 64, c2, c3);
        tma_reduce_4d(&p.outn, st + 4096, 512 + 32 * t, c2, c3);
        asm volatile("cp.async.bulk.commit_group;" ::: "memory");
        asm volatile("cp.async.bulk.wait_group.read 0;" ::: "memory");
      }
      __syncwarp();
    }
    if ((w8 & 3) == 0 && lane == 0) TR(400 + 20 * cw + 8);
    if (tid == 128) atomicAdd(&g_done, 1u);
  }
}

typedef CUresult (*PFN_encodeTiled)(CUtensorMap*, CUtensorMapDataType, cuuint32_t, void*, const cuuint64_t*, const cuuint64_t*,
                                    const cuuint32_t*, const cuuint32_t*, CUtensorMapInterleave, CUtensorMapSwizzle,
                                    CUtensorMapL2promotion, CUtensorMapFloatOOBfill);

void encode(PFN_encodeTiled fn, CUtensorMap* m, const void* base, int rank, const cuuint64_t* dims, const cuuint64_t* strides,
            const cuuint32_t* box, CUtensorMapSwizzle swz) {
  cuuint32_t es[5] = {1, 1, 1, 1, 1};
  fn(m, CU_TENSOR_MAP_DATA_TYPE_BFLOAT16, rank, const_cast<void*>(base), dims, strides, box, es, CU_TENSOR_MAP_INTERLEAVE_NONE, swz,
     CU_TENSOR_MAP_L2_PROMOTION_L2_128B, CU_TENSOR_MAP_FLOAT_OOB_FILL_NONE);
}
void encode4d(PFN_encodeTiled fn, CUtensorMap* m, const void* base, uint64_t d0, uint64_t d1, uint64_t d2, uint64_t d3, uint64_t s1, uint64_t s2, uint64_t s3,
              uint32_t b0, uint32_t b1, uint32_t b2, uint32_t b3, CUtensorMapSwizzle swz) {
  cuuint64_t dims[4] = {d0, d1, d2, d3}; cuuint64_t st[3] = {s1, s2, s3}; cuuint32_t box[4] = {b0, b1, b2, b3};
  encode(fn, m, base, 4, dims, st, box, swz);
}

}

extern "C" void kernel_launch(void* const* d_in, const int* in_sizes, int n_in, void* d_out, int out_size) {
  static Params prm;
  static void* cached[10] = {};
  static bool attr_done = false;
  bool same = attr_done;
  for (int k = 0; k < 9; k++) same = same && cached[k] == d_in[k];
  same = same && cached[9] == d_out;
  if (!same) {
    void* fnp = nullptr;
    cudaDriverEntryPointQueryResult qr;
    cudaGetDriverEntryPoint("cuTensorMapEncodeTiled", &fnp, cudaEnableDefault, &qr);
    PFN_encodeTiled fn = (PFN_encodeTiled)fnp;
    const __nv_bfloat16* ax = (const __nv_bfloat16*)d_in[0];
    const __nv_bfloat16* wqkv = (const __nv_bfloat16*)d_in[1];
    const __nv_bfloat16* wo = (const __nv_bfloat16*)d_in[2];
    const __nv_bfloat16* w1 = (const __nv_bfloat16*)d_in[4];
    const __nv_bfloat16* w2 = (const __nv_bfloat16*)d_in[6];
    void *hp = nullptr, *op = nullptr;
    cudaGetSymbolAddress(&hp, g_H);
    cudaGetSymbolAddress(&op, g_O);
    const CUtensorMapSwizzle S128 = CU_TENSOR_MAP_SWIZZLE_128B, S64 = CU_TENSOR_MAP_SWIZZLE_64B, S0 = CU_TENSOR_MAP_SWIZZLE_NONE;
    encode4d(fn, &prm.a[0], ax, DM, 16, 2, SEQ / 32, 2 * DM * 2, DM * 2, 32 * DM * 2, 64, 16, 2, 4, S128);
    encode4d(fn, &prm.a[1], hp, FF, 16, 2, SEQ / 32, FF * 2, 16 * FF * 2, 32 * FF * 2, 64, 16, 2, 4, S128);
    encode4d(fn, &prm.a[2], op, DM, 16, 2, SEQ / 32, DM * 2, 16 * DM * 2, 32 * DM * 2, 64, 16, 2, 4, S128);
    encode4d(fn, &prm.hst, hp, FF, 16, 2, SEQ / 32, FF * 2, 16 * FF * 2, 32 * FF * 2, 64, 16, 2, 1, S128);
    encode4d(fn, &prm.ost, op, DM, 16, 2, SEQ / 32, DM * 2, 16 * DM * 2, 32 * DM * 2, 80, 16, 2, 4, S0);
    encode4d(fn, &prm.outw, d_out, DM, 16, 2, SEQ / 32, 2 * DM * 2, DM * 2, 32 * DM * 2, 64, 16, 1, 1, S128);
    encode4d(fn, &prm.outn, d_out, DM, 16, 2, SEQ / 32, 2 * DM * 2, DM * 2, 32 * DM * 2, 32, 16, 1, 1, S64);
    encode4d(fn, &prm.w[0], w1, 64, DM, 3, 8, FF * 2, 128, 384, 64, 32, 3, 1, S128);
    encode4d(fn, &prm.w[1], w1 + 1536, 24, DM, 1, 8, FF * 2, 128, 48, NBOX1, 32, 1, 1, S128);
    encode4d(fn, &prm.w[2], wqkv, 64, DM, 3, 8, 3 * DM * 2, DM * 2, 160, 64, 32, 3, 1, S128);
    encode4d(fn, &prm.w[3], wqkv + 64, 16, DM, 3, 8, 3 * DM * 2, DM * 2, 160, 16, 32, 3, 1, CU_TENSOR_MAP_SWIZZLE_32B);
    encode4d(fn, &prm.w[4], w2, 64, FF, 2, 4, DM * 2, 128, 256, 64, 32, 2, 1, S128);
    encode4d(fn, &prm.w[5], w2 + 512, 32, FF, 1, 4, DM * 2, 128, 64, NBOX2, 32, 1, 1, S128);
    encode4d(fn, &prm.w[6], wo, 64, DM, 2, 4, DM * 2, 128, 256, 64, 32, 2, 1, S128);
    encode4d(fn, &prm.w[7], wo + 512, 32, DM, 1, 4, DM * 2, 128, 64, NBOX2, 32, 1, 1, S128);
    prm.pwqkv = wqkv; prm.pwo = wo; prm.pw2 = w2;
    cudaFuncSetAttribute(fused_kernel, cudaFuncAttributeMaxDynamicSharedMemorySize, SMEM_BYTES);
    for (int k = 0; k < 9; k++) cached[k] = d_in[k];
    cached[9] = d_out;
    attr_done = true;
  }
  cudaLaunchConfig_t cfg = {};
  cfg.gridDim = dim3(NCTA);
  cfg.blockDim = dim3(NTHREADS);
  cfg.dynamicSmemBytes = SMEM_BYTES;
  cfg.stream = cudaStreamPerThread;
  cudaLaunchKernelEx(&cfg, fused_kernel, (const __nv_bfloat16*)d_in[0], (const __nv_bfloat16*)d_in[4], (const __nv_bfloat16*)d_in[5],
                     (const __nv_bfloat16*)d_in[8], (__nv_bfloat16*)d_out, (const __nv_bfloat16*)d_in[7], prm);
}
```

```cpp
#include <cuda_runtime.h>
#include <cuda_bf16.h>
#include <cuda.h>
#include <stdint.h>

namespace {

constexpr int SEQ = 2048, DM = 640, FF = 1728;
constexpr int NCTA = 128;
constexpr int NTHREADS = 384;

constexpr uint32_t PAGE = 16384;
constexpr int NA = 4, NW = 7;
constexpr uint32_t WB = NA * PAGE;
constexpr uint32_t R0 = (NA + NW) * PAGE;
constexpr uint32_t PLANE = 72 * 160 + 18 * 16;
constexpr uint32_t BAR_OFF = R0 + 49152;
constexpr uint32_t G_OFF = BAR_OFF + 256;
constexpr uint32_t TAG_OFF = BAR_OFF + 240;
constexpr uint32_t BIAS_OFF = G_OFF + 256;
constexpr uint32_t SMEM_BYTES = BIAS_OFF + 768;
static_assert(SMEM_BYTES <= 232448 && R0 % 1024 == 0 && 4 * PLANE <= 49152, "smem");

enum { B_AF = 0, B_AE = 4, B_WF = 8, B_WE = 15, B_GREADY = 22, B_HDONE = 23, B_HFREE = 24, B_HALO = 25, B_ODONE = 26, B_XG = 27, B_KV = 28, B_NBAR = 29 };
#define NBOX1 24
#define NBOX2 32
constexpr uint32_t BYTES_W1 = 12288 + NBOX1 * 64, BYTES_W2 = 8192 + NBOX2 * 64;
constexpr int N_H = 20, N_QKV = 20, N_P3 = 37;
#define ATTPOS 10
constexpr int ATT_POS = ATTPOS;
#define HPACE 600
constexpr uint32_t H_PACE = HPACE;

struct Params {
  CUtensorMap w[8];
  CUtensorMap a[3];
  CUtensorMap hst, ost, outw, outn;
  const __nv_bfloat16 *pwqkv, *pwo, *pw2;
};

__device__ __align__(1024) __nv_bfloat16 g_H[SEQ * FF];
__device__ __align__(1024) __nv_bfloat16 g_O[SEQ * DM];
__device__ __align__(128) unsigned long long g_gateLL[SEQ];
__device__ __align__(128) ulonglong2 g_halo[128 * 2 * 10 * 32];
__device__ __align__(128) uint32_t g_flag[16 * 32];
__device__ __align__(128) uint32_t g_done;

#define TR(slot) do {} while (0)
#define TRW(slot) do {} while (0)
__device__ __forceinline__ uint32_t smem_u32(const void* p) { return (uint32_t)__cvta_generic_to_shared(p); }
__device__ __forceinline__ void mbar_init(uint32_t bar, uint32_t cnt) { asm volatile("mbarrier.init.shared::cta.b64 [%0], %1;" ::"r"(bar), "r"(cnt) : "memory"); }
__device__ __forceinline__ void mbar_expect_tx(uint32_t bar, uint32_t bytes) { asm volatile("mbarrier.arrive.expect_tx.shared::cta.b64 _, [%0], %1;" ::"r"(bar), "r"(bytes) : "memory"); }
__device__ __forceinline__ void mbar_arrive(uint32_t bar) { asm volatile("mbarrier.arrive.shared::cta.b64 _, [%0];" ::"r"(bar) : "memory"); }
__device__ __forceinline__ uint32_t mapa(uint32_t addr, uint32_t cta) { uint32_t r; asm volatile("mapa.shared::cluster.u32 %0, %1, %2;" : "=r"(r) : "r"(addr), "r"(cta)); return r; }
__device__ __forceinline__ void mbar_arrive_remote(uint32_t rbar) { asm volatile("mbarrier.arrive.shared::cluster.b64 _, [%0];" ::"r"(rbar) : "memory"); }
constexpr uint32_t SPIN_MAX = 1u << 21;
__device__ __forceinline__ void mbar_wait(uint32_t bar, uint32_t parity, uint32_t& n) {
  asm volatile("{\n.reg .pred p, q;\nLAB_WAIT:\n"
               "mbarrier.try_wait.parity.shared::cta.b64 p, [%1], %2;\n"
               "add.u32 %0, %0, 1;\nsetp.lt.and.u32 q, %0, %3, !p;\n@q bra LAB_WAIT;\n}" : "+r"(n) : "r"(bar), "r"(parity), "n"(SPIN_MAX) : "memory");
}
__device__ __forceinline__ bool elect_one() {
  uint32_t p;
  asm volatile("{\n.reg .pred P;\nelect.sync _|P, 0xffffffff;\nselp.u32 %0, 1, 0, P;\n}" : "=r"(p));
  return p;
}
__device__ __forceinline__ void tma_4d(uint32_t dst, const CUtensorMap* tm, int c0, int c1, int c2, int c3, uint32_t bar) {
  asm volatile("cp.async.bulk.tensor.4d.shared::cluster.global.mbarrier::complete_tx::bytes [%0], [%1, {%3, %4, %5, %6}], [%2];"
               ::"r"(dst), "l"(tm), "r"(bar), "r"(c0), "r"(c1), "r"(c2), "r"(c3) : "memory");
}
__device__ __forceinline__ void tma_4d_mc(uint32_t dst, const CUtensorMap* tm, int c0, int c1, int c2, int c3, uint32_t bar) {
  asm volatile("cp.async.bulk.tensor.4d.shared::cluster.global.mbarrier::complete_tx::bytes.multicast::cluster [%0], [%1, {%3, %4, %5, %6}], [%2], %7;"
               ::"r"(dst), "l"(tm), "r"(bar), "r"(c0), "r"(c1), "r"(c2), "r"(c3), "h"((uint16_t)3) : "memory");
}
__device__ __forceinline__ void tma_store_4d(const CUtensorMap* tm, uint32_t src, int c0, int c1, int c2, int c3) {
  asm volatile("cp.async.bulk.tensor.4d.global.shared::cta.bulk_group [%0, {%2, %3, %4, %5}], [%1];" ::"l"(tm), "r"(src), "r"(c0), "r"(c1), "r"(c2), "r"(c3) : "memory");
}
__device__ __forceinline__ void tma_reduce_4d(const CUtensorMap* tm, uint32_t src, int c0, int c2, int c3) {
  asm volatile("cp.reduce.async.bulk.tensor.4d.global.shared::cta.add.bulk_group [%0, {%2, %5, %3, %4}], [%1];" ::"l"(tm), "r"(src), "r"(c0), "r"(c2), "r"(c3), "r"(0) : "memory");
}
__device__ __forceinline__ void bulk_load(uint32_t dst, const void* src, uint32_t bytes, uint32_t bar) {
  asm volatile("cp.async.bulk.shared::cluster.global.mbarrier::complete_tx::bytes [%0], [%1], %2, [%3];" ::"r"(dst), "l"(src), "r"(bytes), "r"(bar) : "memory");
}
__device__ __forceinline__ void bulk_store(void* dst, uint32_t src, uint32_t bytes) {
  asm volatile("cp.async.bulk.global.shared::cta.bulk_group [%0], [%1], %2;" ::"l"(dst), "r"(src), "r"(bytes) : "memory");
}
__device__ __forceinline__ void l2_prefetch(const void* src, uint32_t bytes) {
  asm volatile("cp.async.bulk.prefetch.L2.global [%0], %1;" ::"l"(src), "r"(bytes) : "memory");
}
__device__ __forceinline__ void cp_async16(uint32_t dst, const void* src) { asm volatile("cp.async.cg.shared.global [%0], [%1], 16;" ::"r"(dst), "l"(src) : "memory"); }
__device__ __forceinline__ void prefetch_tmap(const CUtensorMap* tm) { asm volatile("prefetch.tensormap [%0];" ::"l"(tm) : "memory"); }
__device__ __forceinline__ void fence_async_smem() { asm volatile("fence.proxy.async.shared::cta;" ::: "memory"); }
__device__ __forceinline__ void fence_async_glob() { asm volatile("fence.proxy.async.global;" ::: "memory"); }
__device__ __forceinline__ void wg_fence() { asm volatile("wgmma.fence.sync.aligned;" ::: "memory"); }
__device__ __forceinline__ void wg_commit() { asm volatile("wgmma.commit_group.sync.aligned;" ::: "memory"); }
template <int N> __device__ __forceinline__ void wg_wait() { asm volatile("wgmma.wait_group.sync.aligned %0;" ::"n"(N) : "memory"); }
__device__ __forceinline__ uint64_t make_desc(uint32_t addr, uint32_t lbo, uint32_t sbo, uint32_t swz  ) {
  return (uint64_t)((addr & 0x3FFFF) >> 4) | ((uint64_t)(lbo >> 4) << 16) | ((uint64_t)(sbo >> 4) << 32) | ((uint64_t)swz << 62);
}
__device__ __forceinline__ void stmatrix_x4(uint32_t addr, uint32_t a, uint32_t b, uint32_t c, uint32_t d) {
  asm volatile("stmatrix.sync.aligned.m8n8.x4.shared.b16 [%0], {%1, %2, %3, %4};" ::"r"(addr), "r"(a), "r"(b), "r"(c), "r"(d) : "memory");
}
__device__ __forceinline__ void ldsm4(uint32_t* d, uint32_t addr) {
  asm volatile("ldmatrix.sync.aligned.m8n8.x4.shared.b16 {%0, %1, %2, %3}, [%4];" : "=r"(d[0]), "=r"(d[1]), "=r"(d[2]), "=r"(d[3]) : "r"(addr) : "memory");
}
__device__ __forceinline__ void ldsm4t(uint32_t* d, uint32_t addr) {
  asm volatile("ldmatrix.sync.aligned.m8n8.x4.trans.shared.b16 {%0, %1, %2, %3}, [%4];" : "=r"(d[0]), "=r"(d[1]), "=r"(d[2]), "=r"(d[3]) : "r"(addr) : "memory");
}
__device__ __forceinline__ void mma16z(float* d, uint32_t a0, uint32_t a1, uint32_t a2, uint32_t a3, uint32_t b0, uint32_t b1) {
  asm volatile("mma.sync.aligned.m16n8k16.row.col.f32.bf16.bf16.f32 {%0, %1, %2, %3}, {%4, %5, %6, %7}, {%8, %9}, {%10, %10, %10, %10};"
               : "=f"(d[0]), "=f"(d[1]), "=f"(d[2]), "=f"(d[3]) : "r"(a0), "r"(a1), "r"(a2), "r"(a3), "r"(b0), "r"(b1), "f"(0.f));
}
__device__ __forceinline__ void mma16(float* d, uint32_t a0, uint32_t a1, uint32_t a2, uint32_t a3, uint32_t b0, uint32_t b1) {
  asm volatile("mma.sync.aligned.m16n8k16.row.col.f32.bf16.bf16.f32 {%0, %1, %2, %3}, {%4, %5, %6, %7}, {%8, %9}, {%0, %1, %2, %3};"
               : "+f"(d[0]), "+f"(d[1]), "+f"(d[2]), "+f"(d[3]) : "r"(a0), "r"(a1), "r"(a2), "r"(a3), "r"(b0), "r"(b1));
}
__device__ __forceinline__ void mma8z(float* d, uint32_t a0, uint32_t a1, uint32_t b0) {
  asm volatile("mma.sync.aligned.m16n8k8.row.col.f32.bf16.bf16.f32 {%0, %1, %2, %3}, {%4, %5}, {%6}, {%7, %7, %7, %7};"
               : "=f"(d[0]), "=f"(d[1]), "=f"(d[2]), "=f"(d[3]) : "r"(a0), "r"(a1), "r"(b0), "f"(0.f));
}
__device__ __forceinline__ void mma8(float* d, uint32_t a0, uint32_t a1, uint32_t b0) {
  asm volatile("mma.sync.aligned.m16n8k8.row.col.f32.bf16.bf16.f32 {%0, %1, %2, %3}, {%4, %5}, {%6}, {%0, %1, %2, %3};"
               : "+f"(d[0]), "+f"(d[1]), "+f"(d[2]), "+f"(d[3]) : "r"(a0), "r"(a1), "r"(b0));
}
__device__ __forceinline__ uint32_t pack_bf16(float lo, float hi) {
  uint32_t r; asm("cvt.rn.bf16x2.f32 %0, %1, %2;" : "=r"(r) : "f"(hi), "f"(lo)); return r;
}
__device__ __forceinline__ uint32_t pack_bf16_relu(float lo, float hi) {
  uint32_t r; asm("cvt.rn.relu.bf16x2.f32 %0, %1, %2;" : "=r"(r) : "f"(hi), "f"(lo)); return r;
}
__device__ __forceinline__ uint32_t add_relu_bf16x2(uint32_t a, uint32_t b) {
  uint32_t r; asm("fma.rn.relu.bf16x2 %0, %1, %2, %3;" : "=r"(r) : "r"(a), "r"(0x3f803f80u), "r"(b)); return r;
}
__device__ __forceinline__ uint32_t fma_bf16x2(uint32_t a, uint32_t b, uint32_t c) {
  uint32_t r; asm("fma.rn.bf16x2 %0, %1, %2, %3;" : "=r"(r) : "r"(a), "r"(b), "r"(c)); return r;
}
__device__ __forceinline__ void prefetch_l2(const void* p) { asm volatile("prefetch.global.L2 [%0];" ::"l"(p)); }
__device__ __forceinline__ uint32_t mul_bf16x2(uint32_t a, uint32_t b) {
  uint32_t r; asm("mul.rn.bf16x2 %0, %1, %2;" : "=r"(r) : "r"(a), "r"(b)); return r;
}
__device__ __forceinline__ float bf_lo(uint32_t w) { return __uint_as_float(w << 16); }
__device__ __forceinline__ float bf_hi(uint32_t w) { return __uint_as_float(w & 0xffff0000u); }
__device__ __forceinline__ uint32_t lds16(uint32_t a) { uint16_t v; asm volatile("ld.shared.u16 %0, [%1];" : "=h"(v) : "r"(a)); return v; }
__device__ __forceinline__ void sts16(uint32_t a, uint16_t v) { asm volatile("st.shared.u16 [%0], %1;" ::"r"(a), "h"(v) : "memory"); }
__device__ __forceinline__ uint32_t ld_acquire(const uint32_t* p) { uint32_t v; asm volatile("ld.acquire.gpu.global.u32 %0, [%1];" : "=r"(v) : "l"(p) : "memory"); return v; }
__device__ __forceinline__ void st_flag(uint32_t* p, uint32_t v) { asm volatile("st.release.gpu.global.u32 [%0], %1;" ::"l"(p), "r"(v) : "memory"); }
__device__ __forceinline__ float ex2(float x) { float r; asm("ex2.approx.ftz.f32 %0, %1;" : "=f"(r) : "f"(x)); return r; }
__device__ __forceinline__ float rcp(float x) { float r; asm("rcp.approx.ftz.f32 %0, %1;" : "=f"(r) : "f"(x)); return r; }
__device__ __forceinline__ uint64_t ld_ll(const unsigned long long* p) { uint64_t v; asm volatile("ld.relaxed.gpu.global.b64 %0, [%1];" : "=l"(v) : "l"(p) : "memory"); return v; }
__device__ __forceinline__ void st_ll(unsigned long long* p, uint32_t x, uint32_t tag) {
  asm volatile("st.relaxed.gpu.global.b64 [%0], %1;" ::"l"(p), "l"(((uint64_t)tag << 32) | x) : "memory");
}
__device__ __forceinline__ uint4 ld_acquire4(const uint32_t* p) {
  uint4 v; asm volatile("ld.acquire.gpu.global.v4.u32 {%0, %1, %2, %3}, [%4];" : "=r"(v.x), "=r"(v.y), "=r"(v.z), "=r"(v.w) : "l"(p) : "memory"); return v;
}
__device__ __forceinline__ ulonglong2 ld_ll2(const ulonglong2* p) {
  ulonglong2 v; asm volatile("ld.relaxed.gpu.global.v2.b64 {%0, %1}, [%2];" : "=l"(v.x), "=l"(v.y) : "l"(p) : "memory"); return v;
}
__device__ __forceinline__ void st_ll2(ulonglong2* p, uint32_t x, uint32_t y, uint32_t tag) {
  asm volatile("st.relaxed.gpu.global.v2.b64 [%0], {%1, %2};" ::"l"(p), "l"(((uint64_t)tag << 32) | x), "l"(((uint64_t)tag << 32) | y) : "memory");
}
__device__ __forceinline__ void sts32(uint32_t a, uint32_t x) { asm volatile("st.shared.u32 [%0], %1;" ::"r"(a), "r"(x) : "memory"); }
__device__ __forceinline__ uint32_t lds32(uint32_t a) { uint32_t v; asm volatile("ld.shared.u32 %0, [%1];" : "=r"(v) : "r"(a) : "memory"); return v; }
__device__ __forceinline__ void sts64(uint32_t a, uint32_t x, uint32_t y) { asm volatile("st.shared.v2.u32 [%0], {%1, %2};" ::"r"(a), "r"(x), "r"(y) : "memory"); }
__device__ __forceinline__ void sts128(uint32_t a, uint4 v) { asm volatile("st.shared.v4.u32 [%0], {%1, %2, %3, %4};" ::"r"(a), "r"(v.x), "r"(v.y), "r"(v.z), "r"(v.w) : "memory"); }
__device__ __forceinline__ uint4 lds128(uint32_t a) { uint4 v; asm volatile("ld.shared.v4.u32 {%0, %1, %2, %3}, [%4];" : "=r"(v.x), "=r"(v.y), "=r"(v.z), "=r"(v.w) : "r"(a) : "memory"); return v; }
__device__ __forceinline__ uint2 lds64(uint32_t a) { uint2 v; asm volatile("ld.shared.v2.u32 {%0, %1}, [%2];" : "=r"(v.x), "=r"(v.y) : "r"(a) : "memory"); return v; }
__device__ __forceinline__ void fence_gpu() { asm volatile("fence.acq_rel.gpu;" ::: "memory"); }
__device__ __forceinline__ void cluster_arrive() { asm volatile("barrier.cluster.arrive.relaxed.aligned;" ::: "memory"); }
__device__ __forceinline__ void cluster_wait() { asm volatile("barrier.cluster.wait.aligned;" ::: "memory"); }
__device__ __forceinline__ uint32_t roff(int r) { return 160 * r + 16 * (r >> 2); }

template <int N> __device__ __forceinline__ void fence_regs(float* a) {
#pragma unroll
  for (int k = 0; k < N; k++) asm volatile("" : "+f"(a[k])::"memory");
}

__device__ __forceinline__ void iter_h(float* d, uint32_t& spin, uint64_t da, uint64_t db, int sc, uint32_t wbar, uint32_t wpar, uint32_t abar, uint32_t apar, uint32_t skipa, uint32_t relbase, int relidx) {
  asm volatile(
    "{\n"
    ".reg .pred s, p, q, r;\n"
    ".reg .b32 a;\n"
    ".reg .b64 da2, db2, dn2;\n"
    "setp.ne.b32 s, %111, 0;\n"
    "wgmma.fence.sync.aligned;\n"
    "wgmma.mma_async.sync.aligned.m64n216k16.f32.bf16.bf16 {%0, %1, %2, %3, %4, %5, %6, %7, %8, %9, %10, %11, %12, %13, %14, %15, %16, %17, %18, %19, %20, %21, %22, %23, %24, %25, %26, %27, %28, %29, %30, %31, %32, %33, %34, %35, %36, %37, %38, %39, %40, %41, %42, %43, %44, %45, %46, %47, %48, %49, %50, %51, %52, %53, %54, %55, %56, %57, %58, %59, %60, %61, %62, %63, %64, %65, %66, %67, %68, %69, %70, %71, %72, %73, %74, %75, %76, %77, %78, %79, %80, %81, %82, %83, %84, %85, %86, %87, %88, %89, %90, %91, %92, %93, %94, %95, %96, %97, %98, %99, %100, %101, %102, %103, %104, %105, %106, %107}, %109, %110, s, 1, 1, 0, 1;\n"
    "mbarrier.test_wait.parity.shared::cta.b64 p, [%112], %113;\n"
    "mbarrier.test_wait.parity.shared::cta.b64 q, [%114], %115;\n"
    "add.s64 da2, %109, 2;\n"
    "add.s64 db2, %110, 128;\n"
    "setp.eq.b32 s, 0, 0;\n"
    "wgmma.mma_async.sync.aligned.m64n216k16.f32.bf16.bf16 {%0, %1, %2, %3, %4, %5, %6, %7, %8, %9, %10, %11, %12, %13, %14, %15, %16, %17, %18, %19, %20, %21, %22, %23, %24, %25, %26, %27, %28, %29, %30, %31, %32, %33, %34, %35, %36, %37, %38, %39, %40, %41, %42, %43, %44, %45, %46, %47, %48, %49, %50, %51, %52, %53, %54, %55, %56, %57, %58, %59, %60, %61, %62, %63, %64, %65, %66, %67, %68, %69, %70, %71, %72, %73, %74, %75, %76, %77, %78, %79, %80, %81, %82, %83, %84, %85, %86, %87, %88, %89, %90, %91, %92, %93, %94, %95, %96, %97, %98, %99, %100, %101, %102, %103, %104, %105, %106, %107}, da2, db2, s, 1, 1, 0, 1;\n"
    "wgmma.commit_group.sync.aligned;\n"
    "setp.ge.s32 r, %118, 0;\n"
    "mad.lo.u32 a, %118, 8, %117;\n"
    "wgmma.wait_group.sync.aligned 1;\n"
    "@r mbarrier.arrive.shared::cluster.b64 _, [a];\n"
    "setp.ne.or.u32 q, %116, 0, q;\n"
    "and.pred r, p, q;\n"
    "@r bra LAB_DONE;\n"
    "LAB_SLOW:\n"
    "@!p mbarrier.try_wait.parity.shared::cta.b64 p, [%112], %113;\n"
    "@!q mbarrier.try_wait.parity.shared::cta.b64 q, [%114], %115;\n"
    "add.u32 %108, %108, 1;\n"
    "and.pred r, p, q;\n"
    "setp.lt.and.u32 r, %108, %119, !r;\n"
    "@r bra LAB_SLOW;\n"
    "LAB_DONE:\n"
    "}\n"
    : "+f"(d[0]), "+f"(d[1]), "+f"(d[2]), "+f"(d[3]), "+f"(d[4]), "+f"(d[5]), "+f"(d[6]), "+f"(d[7]), "+f"(d[8]), "+f"(d[9]), "+f"(d[10]), "+f"(d[11]), "+f"(d[12]), "+f"(d[13]), "+f"(d[14]), "+f"(d[15]), "+f"(d[16]), "+f"(d[17]), "+f"(d[18]), "+f"(d[19]), "+f"(d[20]), "+f"(d[21]), "+f"(d[22]), "+f"(d[23]), "+f"(d[24]), "+f"(d[25]), "+f"(d[26]), "+f"(d[27]), "+f"(d[28]), "+f"(d[29]), "+f"(d[30]), "+f"(d[31]), "+f"(d[32]), "+f"(d[33]), "+f"(d[34]), "+f"(d[35]), "+f"(d[36]), "+f"(d[37]), "+f"(d[38]), "+f"(d[39]), "+f"(d[40]), "+f"(d[41]), "+f"(d[42]), "+f"(d[43]), "+f"(d[44]), "+f"(d[45]), "+f"(d[46]), "+f"(d[47]), "+f"(d[48]), "+f"(d[49]), "+f"(d[50]), "+f"(d[51]), "+f"(d[52]), "+f"(d[53]), "+f"(d[54]), "+f"(d[55]), "+f"(d[56]), "+f"(d[57]), "+f"(d[58]), "+f"(d[59]), "+f"(d[60]), "+f"(d[61]), "+f"(d[62]), "+f"(d[63]), "+f"(d[64]), "+f"(d[65]), "+f"(d[66]), "+f"(d[67]), "+f"(d[68]), "+f"(d[69]), "+f"(d[70]), "+f"(d[71]), "+f"(d[72]), "+f"(d[73]), "+f"(d[74]), "+f"(d[75]), "+f"(d[76]), "+f"(d[77]), "+f"(d[78]), "+f"(d[79]), "+f"(d[80]), "+f"(d[81]), "+f"(d[82]), "+f"(d[83]), "+f"(d[84]), "+f"(d[85]), "+f"(d[86]), "+f"(d[87]), "+f"(d[88]), "+f"(d[89]), "+f"(d[90]), "+f"(d[91]), "+f"(d[92]), "+f"(d[93]), "+f"(d[94]), "+f"(d[95]), "+f"(d[96]), "+f"(d[97]), "+f"(d[98]), "+f"(d[99]), "+f"(d[100]), "+f"(d[101]), "+f"(d[102]), "+f"(d[103]), "+f"(d[104]), "+f"(d[105]), "+f"(d[106]), "+f"(d[107]), "+r"(spin)
    : "l"(da), "l"(db), "r"(sc), "r"(wbar), "r"(wpar), "r"(abar), "r"(apar), "r"(skipa), "r"(relbase), "r"(relidx), "n"(SPIN_MAX)
    : "memory");
}
__device__ __forceinline__ void iter_q(float* d, uint32_t& spin, uint64_t da, uint64_t db, uint64_t dn, int sc, uint32_t wbar, uint32_t wpar, uint32_t abar, uint32_t apar, uint32_t skipa, uint32_t relbase, int relidx) {
  asm volatile(
    "{\n"
    ".reg .pred s, p, q, r;\n"
    ".reg .b32 a;\n"
    ".reg .b64 da2, db2, dn2;\n"
    "setp.ne.b32 s, %124, 0;\n"
    "wgmma.fence.sync.aligned;\n"
    "wgmma.mma_async.sync.aligned.m64n192k16.f32.bf16.bf16 {%0, %1, %2, %3, %4, %5, %6, %7, %8, %9, %10, %11, %12, %13, %14, %15, %16, %17, %18, %19, %20, %21, %22, %23, %24, %25, %26, %27, %28, %29, %30, %31, %32, %33, %34, %35, %36, %37, %38, %39, %40, %41, %42, %43, %44, %45, %46, %47, %48, %49, %50, %51, %52, %53, %54, %55, %56, %57, %58, %59, %60, %61, %62, %63, %64, %65, %66, %67, %68, %69, %70, %71, %72, %73, %74, %75, %76, %77, %78, %79, %80, %81, %82, %83, %84, %85, %86, %87, %88, %89, %90, %91, %92, %93, %94, %95}, %121, %122, s, 1, 1, 0, 1;\n"
    "wgmma.mma_async.sync.aligned.m64n48k16.f32.bf16.bf16 {%96, %97, %98, %99, %100, %101, %102, %103, %104, %105, %106, %107, %108, %109, %110, %111, %112, %113, %114, %115, %116, %117, %118, %119}, %121, %123, s, 1, 1, 0, 1;\n"
    "mbarrier.test_wait.parity.shared::cta.b64 p, [%125], %126;\n"
    "mbarrier.test_wait.parity.shared::cta.b64 q, [%127], %128;\n"
    "add.s64 da2, %121, 2;\n"
    "add.s64 db2, %122, 128;\n"
    "add.s64 dn2, %123, 32;\n"
    "setp.eq.b32 s, 0, 0;\n"
    "wgmma.mma_async.sync.aligned.m64n192k16.f32.bf16.bf16 {%0, %1, %2, %3, %4, %5, %6, %7, %8, %9, %10, %11, %12, %13, %14, %15, %16, %17, %18, %19, %20, %21, %22, %23, %24, %25, %26, %27, %28, %29, %30, %31, %32, %33, %34, %35, %36, %37, %38, %39, %40, %41, %42, %43, %44, %45, %46, %47, %48, %49, %50, %51, %52, %53, %54, %55, %56, %57, %58, %59, %60, %61, %62, %63, %64, %65, %66, %67, %68, %69, %70, %71, %72, %73, %74, %75, %76, %77, %78, %79, %80, %81, %82, %83, %84, %85, %86, %87, %88, %89, %90, %91, %92, %93, %94, %95}, da2, db2, s, 1, 1, 0, 1;\n"
    "wgmma.mma_async.sync.aligned.m64n48k16.f32.bf16.bf16 {%96, %97, %98, %99, %100, %101, %102, %103, %104, %105, %106, %107, %108, %109, %110, %111, %112, %113, %114, %115, %116, %117, %118, %119}, da2, dn2, s, 1, 1, 0, 1;\n"
    "wgmma.commit_group.sync.aligned;\n"
    "setp.ge.s32 r, %131, 0;\n"
    "mad.lo.u32 a, %131, 8, %130;\n"
    "wgmma.wait_group.sync.aligned 1;\n"
    "@r mbarrier.arrive.shared::cluster.b64 _, [a];\n"
    "setp.ne.or.u32 q, %129, 0, q;\n"
    "and.pred r, p, q;\n"
    "@r bra LAB_DONE;\n"
    "LAB_SLOW:\n"
    "@!p mbarrier.try_wait.parity.shared::cta.b64 p, [%125], %126;\n"
    "@!q mbarrier.try_wait.parity.shared::cta.b64 q, [%127], %128;\n"
    "add.u32 %120, %120, 1;\n"
    "and.pred r, p, q;\n"
    "setp.lt.and.u32 r, %120, %132, !r;\n"
    "@r bra LAB_SLOW;\n"
    "LAB_DONE:\n"
    "}\n"
    : "+f"(d[0]), "+f"(d[1]), "+f"(d[2]), "+f"(d[3]), "+f"(d[4]), "+f"(d[5]), "+f"(d[6]), "+f"(d[7]), "+f"(d[8]), "+f"(d[9]), "+f"(d[10]), "+f"(d[11]), "+f"(d[12]), "+f"(d[13]), "+f"(d[14]), "+f"(d[15]), "+f"(d[16]), "+f"(d[17]), "+f"(d[18]), "+f"(d[19]), "+f"(d[20]), "+f"(d[21]), "+f"(d[22]), "+f"(d[23]), "+f"(d[24]), "+f"(d[25]), "+f"(d[26]), "+f"(d[27]), "+f"(d[28]), "+f"(d[29]), "+f"(d[30]), "+f"(d[31]), "+f"(d[32]), "+f"(d[33]), "+f"(d[34]), "+f"(d[35]), "+f"(d[36]), "+f"(d[37]), "+f"(d[38]), "+f"(d[39]), "+f"(d[40]), "+f"(d[41]), "+f"(d[42]), "+f"(d[43]), "+f"(d[44]), "+f"(d[45]), "+f"(d[46]), "+f"(d[47]), "+f"(d[48]), "+f"(d[49]), "+f"(d[50]), "+f"(d[51]), "+f"(d[52]), "+f"(d[53]), "+f"(d[54]), "+f"(d[55]), "+f"(d[56]), "+f"(d[57]), "+f"(d[58]), "+f"(d[59]), "+f"(d[60]), "+f"(d[61]), "+f"(d[62]), "+f"(d[63]), "+f"(d[64]), "+f"(d[65]), "+f"(d[66]), "+f"(d[67]), "+f"(d[68]), "+f"(d[69]), "+f"(d[70]), "+f"(d[71]), "+f"(d[72]), "+f"(d[73]), "+f"(d[74]), "+f"(d[75]), "+f"(d[76]), "+f"(d[77]), "+f"(d[78]), "+f"(d[79]), "+f"(d[80]), "+f"(d[81]), "+f"(d[82]), "+f"(d[83]), "+f"(d[84]), "+f"(d[85]), "+f"(d[86]), "+f"(d[87]), "+f"(d[88]), "+f"(d[89]), "+f"(d[90]), "+f"(d[91]), "+f"(d[92]), "+f"(d[93]), "+f"(d[94]), "+f"(d[95]), "+f"(d[96]), "+f"(d[97]), "+f"(d[98]), "+f"(d[99]), "+f"(d[100]), "+f"(d[101]), "+f"(d[102]), "+f"(d[103]), "+f"(d[104]), "+f"(d[105]), "+f"(d[106]), "+f"(d[107]), "+f"(d[108]), "+f"(d[109]), "+f"(d[110]), "+f"(d[111]), "+f"(d[112]), "+f"(d[113]), "+f"(d[114]), "+f"(d[115]), "+f"(d[116]), "+f"(d[117]), "+f"(d[118]), "+f"(d[119]), "+r"(spin)
    : "l"(da), "l"(db), "l"(dn), "r"(sc), "r"(wbar), "r"(wpar), "r"(abar), "r"(apar), "r"(skipa), "r"(relbase), "r"(relidx), "n"(SPIN_MAX)
    : "memory");
}
__device__ __forceinline__ void iter_p(float* d, uint32_t& spin, uint64_t da, uint64_t db, int sc, uint32_t wbar, uint32_t wpar, uint32_t abar, uint32_t apar, uint32_t skipa, uint32_t relbase, int relidx, uint32_t skipw) {
  asm volatile(
    "{\n"
    ".reg .pred s, p, q, r;\n"
    ".reg .b32 a;\n"
    ".reg .b64 da2, db2, dn2;\n"
    "setp.ne.b32 s, %83, 0;\n"
    "wgmma.fence.sync.aligned;\n"
    "wgmma.mma_async.sync.aligned.m64n160k16.f32.bf16.bf16 {%0, %1, %2, %3, %4, %5, %6, %7, %8, %9, %10, %11, %12, %13, %14, %15, %16, %17, %18, %19, %20, %21, %22, %23, %24, %25, %26, %27, %28, %29, %30, %31, %32, %33, %34, %35, %36, %37, %38, %39, %40, %41, %42, %43, %44, %45, %46, %47, %48, %49, %50, %51, %52, %53, %54, %55, %56, %57, %58, %59, %60, %61, %62, %63, %64, %65, %66, %67, %68, %69, %70, %71, %72, %73, %74, %75, %76, %77, %78, %79}, %81, %82, s, 1, 1, 0, 1;\n"
    "mbarrier.test_wait.parity.shared::cta.b64 p, [%84], %85;\n"
    "mbarrier.test_wait.parity.shared::cta.b64 q, [%86], %87;\n"
    "add.s64 da2, %81, 2;\n"
    "add.s64 db2, %82, 128;\n"
    "setp.eq.b32 s, 0, 0;\n"
    "wgmma.mma_async.sync.aligned.m64n160k16.f32.bf16.bf16 {%0, %1, %2, %3, %4, %5, %6, %7, %8, %9, %10, %11, %12, %13, %14, %15, %16, %17, %18, %19, %20, %21, %22, %23, %24, %25, %26, %27, %28, %29, %30, %31, %32, %33, %34, %35, %36, %37, %38, %39, %40, %41, %42, %43, %44, %45, %46, %47, %48, %49, %50, %51, %52, %53, %54, %55, %56, %57, %58, %59, %60, %61, %62, %63, %64, %65, %66, %67, %68, %69, %70, %71, %72, %73, %74, %75, %76, %77, %78, %79}, da2, db2, s, 1, 1, 0, 1;\n"
    "wgmma.commit_group.sync.aligned;\n"
    "setp.ge.s32 r, %90, 0;\n"
    "mad.lo.u32 a, %90, 8, %89;\n"
    "wgmma.wait_group.sync.aligned 1;\n"
    "@r mbarrier.arrive.shared::cluster.b64 _, [a];\n"
    "setp.ne.or.u32 p, %91, 0, p;\n"
    "setp.ne.or.u32 q, %88, 0, q;\n"
    "and.pred r, p, q;\n"
    "@r bra LAB_DONE;\n"
    "LAB_SLOW:\n"
    "@!p mbarrier.try_wait.parity.shared::cta.b64 p, [%84], %85;\n"
    "@!q mbarrier.try_wait.parity.shared::cta.b64 q, [%86], %87;\n"
    "add.u32 %80, %80, 1;\n"
    "and.pred r, p, q;\n"
    "setp.lt.and.u32 r, %80, %92, !r;\n"
    "@r bra LAB_SLOW;\n"
    "LAB_DONE:\n"
    "}\n"
    : "+f"(d[0]), "+f"(d[1]), "+f"(d[2]), "+f"(d[3]), "+f"(d[4]), "+f"(d[5]), "+f"(d[6]), "+f"(d[7]), "+f"(d[8]), "+f"(d[9]), "+f"(d[10]), "+f"(d[11]), "+f"(d[12]), "+f"(d[13]), "+f"(d[14]), "+f"(d[15]), "+f"(d[16]), "+f"(d[17]), "+f"(d[18]), "+f"(d[19]), "+f"(d[20]), "+f"(d[21]), "+f"(d[22]), "+f"(d[23]), "+f"(d[24]), "+f"(d[25]), "+f"(d[26]), "+f"(d[27]), "+f"(d[28]), "+f"(d[29]), "+f"(d[30]), "+f"(d[31]), "+f"(d[32]), "+f"(d[33]), "+f"(d[34]), "+f"(d[35]), "+f"(d[36]), "+f"(d[37]), "+f"(d[38]), "+f"(d[39]), "+f"(d[40]), "+f"(d[41]), "+f"(d[42]), "+f"(d[43]), "+f"(d[44]), "+f"(d[45]), "+f"(d[46]), "+f"(d[47]), "+f"(d[48]), "+f"(d[49]), "+f"(d[50]), "+f"(d[51]), "+f"(d[52]), "+f"(d[53]), "+f"(d[54]), "+f"(d[55]), "+f"(d[56]), "+f"(d[57]), "+f"(d[58]), "+f"(d[59]), "+f"(d[60]), "+f"(d[61]), "+f"(d[62]), "+f"(d[63]), "+f"(d[64]), "+f"(d[65]), "+f"(d[66]), "+f"(d[67]), "+f"(d[68]), "+f"(d[69]), "+f"(d[70]), "+f"(d[71]), "+f"(d[72]), "+f"(d[73]), "+f"(d[74]), "+f"(d[75]), "+f"(d[76]), "+f"(d[77]), "+f"(d[78]), "+f"(d[79]), "+r"(spin)
    : "l"(da), "l"(db), "r"(sc), "r"(wbar), "r"(wpar), "r"(abar), "r"(apar), "r"(skipa), "r"(relbase), "r"(relidx), "r"(skipw), "n"(SPIN_MAX)
    : "memory");
}

__device__ __forceinline__ void softmax_head(const float (*s)[4], bool gt0, bool gt1, bool first, float glo, float ghi, uint32_t& plo, uint32_t& phi) {
  constexpr float C = 0.22360679774997896f * 1.4426950408889634f;
  float v0 = gt0 ? s[0][0] : s[1][0], v1 = gt1 ? s[0][1] : s[1][1];
  const float v2 = gt0 ? s[1][2] : s[2][2], v3 = gt1 ? s[1][3] : s[2][3];
  if (first) {
    if (gt0) v0 = -1e9f;
    if (gt1) v1 = -1e9f;
  }
  float ml = fmaxf(v0, v1), mh = fmaxf(v2, v3);
  ml = fmaxf(ml, __shfl_xor_sync(0xffffffffu, ml, 1)); mh = fmaxf(mh, __shfl_xor_sync(0xffffffffu, mh, 1));
  ml = fmaxf(ml, __shfl_xor_sync(0xffffffffu, ml, 2)); mh = fmaxf(mh, __shfl_xor_sync(0xffffffffu, mh, 2));
  ml *= C; mh *= C;
  const float e0 = ex2(fmaf(v0, C, -ml)), e1 = ex2(fmaf(v1, C, -ml)), e2 = ex2(fmaf(v2, C, -mh)), e3 = ex2(fmaf(v3, C, -mh));
  float sl = e0 + e1, sh = e2 + e3;
  sl += __shfl_xor_sync(0xffffffffu, sl, 1); sh += __shfl_xor_sync(0xffffffffu, sh, 1);
  sl += __shfl_xor_sync(0xffffffffu, sl, 2); sh += __shfl_xor_sync(0xffffffffu, sh, 2);
  const float fl = glo * rcp(sl), fh = ghi * rcp(sh);
  plo = pack_bf16(e0 * fl, e1 * fl);
  phi = pack_bf16(e2 * fh, e3 * fh);
}
__device__ __forceinline__ void pv_head(float (*o)[4], uint32_t plo, uint32_t phi, uint32_t M, const uint32_t (*v)[5], int c0) {
  const uint32_t a0 = plo & M, a2 = plo & ~M, a3 = phi & M, a5 = phi & ~M;
#pragma unroll
  for (int c = 0; c < 3; c++) mma16z(o[c], a0, 0u, a2, a3, v[0][c0 + c], v[1][c0 + c]);
#pragma unroll
  for (int c = 0; c < 3; c++) mma8(o[c], 0u, a5, v[2][c0 + c]);
}
__device__ __forceinline__ void attention(uint32_t* q, uint32_t kplane, int lane, bool first, float glo, float ghi) {
  const int rho = lane >> 2, qd = lane & 3, m = lane >> 3, row = lane & 7;
  const bool gt0 = 2 * qd > rho, gt1 = 2 * qd + 1 > rho;
  const uint32_t M = (gt0 ? 0xffffu : 0u) | (gt1 ? 0xffff0000u : 0u);
  const uint32_t mA = qd < 2 ? 0xffffffffu : 0u;
  const uint32_t ra = kplane + 160 * row + 16 * (row >> 2);
  uint32_t aA = ra + 16 * m, aB = ra + 1312 * (m < 2 ? m : 2) + 64;
#pragma unroll 1
  for (int pr = 0; pr < 2; pr++) {
    uint32_t plo0, phi0, plo1, phi1;
    {
      uint32_t k[3][5], kb[4];
#pragma unroll
      for (int t = 0; t < 3; t++) ldsm4(k[t], aA + 1312 * t);
      ldsm4(kb, aB);
#pragma unroll
      for (int t = 0; t < 3; t++) k[t][4] = kb[t];
      float s0[3][4], s1[3][4];
#pragma unroll
      for (int t = 0; t < 3; t++) {
        mma16z(s0[t], q[0], q[1], q[2], q[3], k[t][0], k[t][1]);
        mma16z(s1[t], q[6], q[7], q[8], q[9], k[t][3], k[t][4]);
      }
#pragma unroll
      for (int t = 0; t < 3; t++) {
        mma8(s0[t], q[4] & mA, q[5] & mA, k[t][2]);
        mma8(s1[t], q[4] & ~mA, q[5] & ~mA, k[t][2]);
      }
      softmax_head(s0, gt0, gt1, first, glo, ghi, plo0, phi0);
      softmax_head(s1, gt0, gt1, first, glo, ghi, plo1, phi1);
    }
    uint32_t v[3][5], vb[4];
#pragma unroll
    for (int t = 0; t < 3; t++) ldsm4t(v[t], aA + 2 * PLANE + 1312 * t);
    ldsm4t(vb, aB + 2 * PLANE);
#pragma unroll
    for (int t = 0; t < 3; t++) v[t][4] = vb[t];
    float o0[3][4], o1[3][4];
    pv_head(o0, plo0, phi0, M, v, 0);
    pv_head(o1, plo1, phi1, M, v, 2);
#pragma unroll
    for (int c = 0; c < 10; c++) q[c] = q[10 + c];
    uint32_t* oo = q + 10;
    oo[0] = pack_bf16(o0[0][0], o0[0][1]); oo[1] = pack_bf16(o0[0][2], o0[0][3]);
    oo[2] = pack_bf16(o0[1][0], o0[1][1]); oo[3] = pack_bf16(o0[1][2], o0[1][3]);
    oo[4] = qd < 2 ? pack_bf16(o0[2][0], o0[2][1]) : pack_bf16(o1[0][0], o1[0][1]);
    oo[5] = qd < 2 ? pack_bf16(o0[2][2], o0[2][3]) : pack_bf16(o1[0][2], o1[0][3]);
    oo[6] = pack_bf16(o1[1][0], o1[1][1]); oo[7] = pack_bf16(o1[1][2], o1[1][3]);
    oo[8] = pack_bf16(o1[2][0], o1[2][1]); oo[9] = pack_bf16(o1[2][2], o1[2][3]);
    aA += 80; aB += 80;
  }
}

__device__ __forceinline__ uint32_t read_tag() { return (*reinterpret_cast<volatile uint32_t*>(&g_done) >> 7) + 1; }
__device__ __forceinline__ uint32_t clock32() { uint32_t c; asm volatile("mov.u32 %0, %%clock;" : "=r"(c)); return c; }

struct Ring {
  int pa;
  int ua;
  int sw;
  uint32_t pw;
  uint32_t spin;
};

template <int PH, class F>
__device__ __forceinline__ void mma_loop(float* acc, Ring& rg, uint32_t bar, uint32_t rel, uint32_t dlo_a, uint32_t dlo_b, int lane, int trbase, F mid) {
  int relidx = -1;
  constexpr int N = PH == 2 ? N_P3 : 20;
  constexpr uint64_t DHI = (uint64_t)((1024u >> 4) | (1u << 30)) << 32;
  uint32_t da = dlo_a + rg.pa * (PAGE >> 4), db = dlo_b + rg.sw * (PAGE >> 4);
  int h = 0;
#pragma unroll 1
  for (int n = 0; n < N; n++) {
    const int curw = (PH == 2 && n >= N_P3 - NW) ? -1 : rg.sw;
    int cura = -1;
    const bool turn = h == 1 || (PH == 2 && n == 26);
    if (turn) {
      if (PH != 0 || n < 12) cura = rg.pa;
      rg.pa = (rg.pa + 1) & 3;
    }
    if (++rg.sw == NW) { rg.sw = 0; rg.pw ^= 1; }
    const bool newa = turn && (PH == 1 ? n >= 7 : n < N - 1);
    if (newa) rg.ua++;
    const uint32_t wbar = bar + 8 * (B_WF + rg.sw), abar = bar + 8 * (B_AF + rg.pa), apar = (rg.ua >> 2) & 1;
    if (PH == 0) iter_h(acc, rg.spin, DHI | da, DHI | db, n != 0, wbar, rg.pw, abar, apar, !newa, rel, relidx);
    if (PH == 1) {
      const uint64_t dn = ((uint64_t)((256u >> 4) | (3u << 30)) << 32) | (((db + 768u) & 0xffffu) | ((1024u >> 4) << 16));
      iter_q(acc, rg.spin, DHI | da, DHI | db, dn, n != 0, wbar, rg.pw, abar, apar, !newa, rel, relidx);
    }
    if (PH == 2) iter_p(acc, rg.spin, DHI | da, DHI | db, n != 0, wbar, rg.pw, abar, apar, !newa, rel, relidx, n == N - 1);
    relidx = lane < 2 ? curw : (lane == 2 ? cura : -1);
    h = turn ? 0 : 1;
    da = dlo_a + rg.pa * (PAGE >> 4) + h * 4;
    db = dlo_b + rg.sw * (PAGE >> 4);
    if (PH == 2 && n == ATT_POS - 1) { wg_wait<0>(); mid(); }
  }
  wg_wait<0>();
  fence_regs<PH == 0 ? 108 : (PH == 1 ? 120 : 80)>(acc);
  if (PH != 2 && relidx >= 0) mbar_arrive_remote(rel + 8 * relidx);
}

__global__ void __cluster_dims__(2, 1, 1) __launch_bounds__(NTHREADS, 1)
fused_kernel(const __nv_bfloat16* __restrict__ px, const __nv_bfloat16* __restrict__ pw1, const __nv_bfloat16* __restrict__ pb1, const __nv_bfloat16* __restrict__ pgate,
             __nv_bfloat16* __restrict__ pout, const __nv_bfloat16* __restrict__ pb2, const __grid_constant__ Params p) {
  extern __shared__ __align__(1024) uint8_t smem_raw[];
  const uint32_t sb = smem_u32(smem_raw);
  const uint32_t bar = sb + BAR_OFF;
  const int tid = threadIdx.x;
  const int warp = __shfl_sync(0xffffffffu, tid >> 5, 0);
  const int lane = tid & 31;
#define TC(v) do {} while (0)
  const int r = blockIdx.x & 1;
  const int c_ = blockIdx.x >> 1;
  const int L = c_ < 4 ? 4 + c_ : (c_ < 36 ? ((c_ - 4) & 7) * 8 + ((c_ - 4) >> 3) : (1 + (c_ - 36) % 7) * 8 + 4 + (c_ - 36) / 7);
  const int G = L >> 3, pp = L & 7;
  const int i = 4 * (G >> 1) + 2 * (pp >> 2) + r;
  const int j = 4 * (G & 1) + (pp & 3);
  const int t = pp & 3, kh = G & 1;
  const uint32_t cs = i * 8 + j;
  uint32_t spin = 0;

  constexpr int N_EARLY = 2;
  const uint8_t* pf = nullptr;
  uint32_t pfs = 0;
  if (warp == 3) {
    pf = lane < 16 ? reinterpret_cast<const uint8_t*>(px) + (16 * cs + lane) * (DM * 2) : reinterpret_cast<const uint8_t*>(pw1) + (cs * 1728 + (lane - 16) * 128);
    pfs = lane < 16 ? 128u : 64u * FF * 2u;
    if (lane < 30) { prefetch_l2(pf); prefetch_l2(pf + pfs); }
  }
  if (warp < 2) {
    if (elect_one()) {
      if (warp == 0) {
        mbar_init(bar + 8 * B_AF, 1);
#pragma unroll
        for (int b = 0; b < N_EARLY; b++) mbar_init(bar + 8 * (B_WF + b), 1);
        fence_async_smem();
        TC(tc1);
        mbar_expect_tx(bar + 8 * B_AF, PAGE);
        tma_4d(sb, &p.a[0], 0, 0, 0, 4 * i, bar + 8 * B_AF);
#pragma unroll
        for (int n = 0; n < N_EARLY; n++) {
          const uint32_t fb = bar + 8 * (B_WF + n), dst = sb + WB + n * PAGE;
          mbar_expect_tx(fb, BYTES_W1);
          tma_4d(dst, &p.w[0], 0, n * 32, 0, j, fb);
          tma_4d(dst + 12288, &p.w[1], 0, n * 32, 0, j, fb);
        }
        TC(tc3);
      } else {
#pragma unroll
        for (int b = 1; b < B_NBAR; b++) {
          if (b >= B_WF && b < B_WF + N_EARLY) continue;
          mbar_init(bar + 8 * b, b >= B_WE && b < B_WE + NW ? 16 : ((b >= B_AE && b < B_AE + NA) || b == B_HDONE || b == B_ODONE ? 8 : (b == B_GREADY || b == B_KV ? 2 : 1)));
        }
      }
      asm volatile("fence.mbarrier_init.release.cluster;" ::: "memory");
      fence_async_smem();
    }
    __syncwarp();
  }
  TC(tc2);
  cluster_arrive();
  TC(tc5);
  if (warp < 4) {
    asm volatile("{\n.reg .pred p;\nsetp.ne.u32 p, %0, 0;\n@p trap;\n}" ::"r"(sb & 1023));
    if (warp != 1) cluster_wait();
    if (warp < 1) {
      if (elect_one()) {
        int sl = N_EARLY; uint32_t ph = 1;
        uint32_t dst0 = sb + WB + (r == 0 ? 0u : 12288u), bytes = BYTES_W1;
        const CUtensorMap* tm = &p.w[r];
        int c3 = j, kn = 32 * N_EARLY, cnt = N_H - N_EARLY;
#pragma unroll 1
        for (int s = 0; s < 5; s++) {
          if (s == 1) { bytes = 15360; kn = 384; cnt = N_QKV; }
          if (s == 2) { c3 = t; dst0 -= 4096 * r; bytes = BYTES_W2; cnt = 24; }
          if (s == 3) { kn = 1536 + 96 * kh; cnt = 3; }
          if (s == 4) { kn = 320 * kh; cnt = 10; }
          if (s != 0 && s != 3) tm += 2;
#pragma unroll 1
          for (int m = 0; m < cnt; m++) {
            int k = kn;
            kn += 32;
            if (s == 1 && kn == DM) kn = 0;
            if (s == 2) k = 768 * kh + 192 * ((t + (m >> 1)) & 3) + 64 * (m >> 3) + 32 * (m & 1);
            mbar_wait(bar + 8 * (B_WE + sl), ph, spin);
            mbar_expect_tx(bar + 8 * (B_WF + sl), bytes);
            tma_4d_mc(dst0 + sl * PAGE, tm, 0, k, 0, c3, bar + 8 * (B_WF + sl));
            if (++sl == NW) { sl = 0; ph ^= 1; }
          }
        }
      }
    } else if (warp < 2) {
      if (elect_one()) {
        const uint32_t* fl = g_flag + i * 32;
#pragma unroll 1
        for (int u = 1; u < 35; u++) {
          if (u == 4) {
#pragma unroll 1
            for (int m = 2; m < 15; m++) prefetch_tmap(reinterpret_cast<const CUtensorMap*>(&p) + m);
          }
          if (u == 6) {
            l2_prefetch(reinterpret_cast<const uint8_t*>(p.pwqkv) + cs * 19200u, 19200);
            l2_prefetch(reinterpret_cast<const uint8_t*>(p.pw2) + cs * 17280u, 17280);
            l2_prefetch(reinterpret_cast<const uint8_t*>(p.pwo) + cs * 6400u, 6400);
          }
          int k = 64 * (u < 10 ? u : u - 10), need = 0, fo = kh;
          const CUtensorMap* tm = &p.a[0];
          if (u >= 16) {
            const int m = u - 16;
            tm = &p.a[1];
            k = 768 * kh + 192 * ((t + m) & 3) + 64 * (m >> 2);
            if ((m & 3) == 0) need = (m >> 2) + 1;
            if (u >= 28) k = 1536 + 96 * kh + 64 * (u - 28);
            if (u == 29) { need = 1; fo = 1 - kh; }
            if (u >= 30) { tm = &p.a[2]; k = 320 * kh + 64 * (u - 30); need = u == 30 ? 4 : 0; fo = 2 + kh; }
          }
          if (need) {
            const uint32_t base = 4 * (read_tag() - 1);
            uint4 v;
            do { v = ld_acquire4(fl + 4 * fo); }
            while (((int)(v.x - base) < need || (int)(v.y - base) < need || (int)(v.z - base) < need || (int)(v.w - base) < need) && ++spin < SPIN_MAX);
            fence_async_glob();
            TR(u == 29 ? 38 : (u == 30 ? 39 : 39 + need));
          }
          const int sl = u & 3;
          mbar_wait(bar + 8 * (B_AE + sl), ((u >> 2) & 1) ^ 1, spin);
          mbar_expect_tx(bar + 8 * (B_AF + sl), PAGE);
          tma_4d(sb + sl * PAGE, tm, k, 0, 0, 4 * i, bar + 8 * (B_AF + sl));
          TRW(150 + u);
        }
      }
    } else {
      const int w2 = warp - 2;
      const uint32_t tag = read_tag();
      {
        mbar_wait(bar + 8 * B_AF, 0, spin);
        if (w2 == 1 && lane < 30) {
#pragma unroll 1
          for (int m = 2; m < 10; m++) prefetch_l2(pf + (size_t)m * pfs);
        }
        if (w2 == 0 && elect_one()) {
          mbar_expect_tx(bar + 8 * B_XG, 17 * DM * 2);
          bulk_load(sb + R0, reinterpret_cast<const uint8_t*>(px) + cs * (16u * DM * 2u), 16 * DM * 2, bar + 8 * B_XG);
          bulk_load(sb + R0 + 16 * DM * 2, pgate, DM * 2, bar + 8 * B_XG);
        }
        {
          const int nw = w2 == 0 ? 24 : 16;
          const __nv_bfloat16* bp = w2 == 0 ? pb1 + (lane < nw ? 192 * j : 1536 + 24 * j - 192) : pb2 + (lane < nw ? 128 * t : 512 + 32 * t - 128);
          if (lane < (w2 == 0 ? 27 : 20)) sts128(sb + BIAS_OFF + 448 * w2 + 16 * lane, __ldg(reinterpret_cast<const uint4*>(bp) + lane));
        }
        mbar_wait(bar + 8 * B_XG, 0, spin);
        float s0 = 0.f, s1 = 0.f;
        const uint32_t xa = sb + R0 + (8 * w2 + (lane >> 2)) * (DM * 2) + 16 * (lane & 3), wa = sb + R0 + 16 * DM * 2 + 16 * (lane & 3);
#pragma unroll 2
        for (int c = 0; c < 20; c++) {
          const uint4 x = lds128(xa + 64 * c), w = lds128(wa + 64 * c);
          const uint32_t a = mul_bf16x2(x.x, w.x), b = mul_bf16x2(x.y, w.y), d = mul_bf16x2(x.z, w.z), e = mul_bf16x2(x.w, w.w);
          s0 += (bf_lo(a) + bf_hi(a)) + (bf_lo(b) + bf_hi(b));
          s1 += (bf_lo(d) + bf_hi(d)) + (bf_lo(e) + bf_hi(e));
        }
        s0 += s1;
        s0 += __shfl_xor_sync(0xffffffffu, s0, 1);
        s0 += __shfl_xor_sync(0xffffffffu, s0, 2);
        if ((lane & 3) == 0) {
          const float z = __bfloat162float(__float2bfloat16(s0));
          const float g = rcp(1.f + ex2(z * -1.4426950408889634f));
          st_ll(&g_gateLL[16 * cs + 8 * w2 + (lane >> 2)], (uint32_t)__bfloat16_as_ushort(__float2bfloat16(g)), tag);
        }
        if (lane == 0 && warp == 2) TR(11);
        {
          const int row = 64 * w2 + 2 * lane;
          ulonglong2 v;
          do { v = ld_ll2(reinterpret_cast<const ulonglong2*>(g_gateLL + (128 * i + row))); }
          while (((uint32_t)(v.x >> 32) != tag || (uint32_t)(v.y >> 32) != tag) && ++spin < SPIN_MAX);
          sts32(sb + G_OFF + 2 * row, (uint32_t)v.x | ((uint32_t)v.y << 16));
        }
        if (lane == 0) sts32(sb + TAG_OFF, tag);
        __syncwarp();
        if (lane == 0) { mbar_arrive(bar + 8 * B_GREADY); if (warp == 2) TR(2); }
        {
          uint4* ow = reinterpret_cast<uint4*>(reinterpret_cast<uint8_t*>(pout) +
                                               (uint32_t)((128 * i + 64 * kh + 32 * w2) * (DM * 2) + (lane < 16 ? 256 * t : 1024 - 256 + 64 * t) + 16 * lane));
          if (lane < 20) {
#pragma unroll 1
            for (int it = 0; it < 32; it++) ow[it * (DM / 8)] = make_uint4(0u, 0u, 0u, 0u);
          }
        }
        if (lane == 0 && warp == 2) TR(13);
        asm volatile("bar.sync 2, 64;" ::: "memory");
      }
      if (w2 == 0) {
        if (elect_one()) {
          uint32_t* flag = g_flag + i * 32 + j;
          mbar_wait(bar + 8 * B_HDONE, 0, spin);
          const uint32_t t0 = clock32();
#pragma unroll 1
          for (int q = 0; q < 12; q++) {
            const int pc = q >> 2;
            while (clock32() - t0 < H_PACE * (uint32_t)q) {}
            tma_store_4d(&p.hst, sb + R0 + q * 4096, 192 * j + 64 * pc, 0, 0, 4 * i + (q & 3));
            asm volatile("cp.async.bulk.commit_group;" ::: "memory");
            if ((q & 3) == 0 && q > 0) {
              asm volatile("cp.async.bulk.wait_group 1;" ::: "memory");
              st_flag(flag, 4 * (tag - 1) + pc);
              TR(44 + pc);
            }
          }
          asm volatile("cp.async.bulk.wait_group.read 0;" ::: "memory");
          mbar_arrive(bar + 8 * B_HFREE);
          asm volatile("cp.async.bulk.wait_group 0;" ::: "memory");
          TR(47);
          st_flag(flag, 4 * tag);
          TR(48);
          mbar_wait(bar + 8 * B_ODONE, 0, spin);
          tma_store_4d(&p.ost, sb + R0, 80 * j, 0, 0, 4 * i);
          asm volatile("cp.async.bulk.commit_group;" ::: "memory");
          asm volatile("cp.async.bulk.wait_group 0;" ::: "memory");
          TR(49);
          st_flag(flag + 8, 4 * tag);
          TR(50);
        }
      } else {
        mbar_wait(bar + 8 * B_KV, 0, spin);
        mbar_wait(bar + 8 * B_HFREE, 0, spin);
        TR(51);
#pragma unroll 1
        for (uint32_t par = 0; par < 2; par++) {
          const ulonglong2* src = g_halo + (((i > 0 ? cs - 8 : cs) * 2 + par) * 320 + lane);
          ulonglong2 v[10];
          uint32_t bad;
          do {
            bad = 0;
#pragma unroll
            for (int c = 0; c < 10; c++) { v[c] = ld_ll2(src + 32 * c); bad |= ((uint32_t)(v[c].x >> 32) ^ tag) | ((uint32_t)(v[c].y >> 32) ^ tag); }
          } while (bad && ++spin < SPIN_MAX);
          const uint32_t dst = sb + R0 + par * PLANE + roff(lane >> 2) + 4 * (lane & 3);
#pragma unroll
          for (int c = 0; c < 10; c++) {
            sts32(dst + (c / 5) * 2 * PLANE + (c % 5) * 32, (uint32_t)v[c].x);
            sts32(dst + (c / 5) * 2 * PLANE + (c % 5) * 32 + 16, (uint32_t)v[c].y);
          }
        }
        __syncwarp();
        if (lane == 0) { mbar_arrive(bar + 8 * B_HALO); TR(54); }
      }
    }
  } else {
    const int w8 = warp - 4, cw = w8 >> 2;
    const uint32_t dlo_a = (((sb + cw * 8192) & 0x3FFFF) >> 4) | (1u << 16);
    const uint32_t dlo_b = (((sb + WB) & 0x3FFFF) >> 4) | ((4096u >> 4) << 16);
    const int trb = 200 + 100 * cw;
    Ring rg = {0, 0, 0, 0u, 0u};
    const int srow = (lane & 7) + 8 * ((lane >> 3) & 1);
    const int prow = 32 * (w8 >> 1) + 2 * (lane >> 2) + (w8 & 1);
    const uint32_t rel = mapa(bar + 8 * (lane < 2 ? B_WE : B_AE), lane == 1 ? 1 - r : r);
    const uint32_t bias = sb + BIAS_OFF + 16 * (lane >> 3);
    auto nomid = []() {};
    TC(tc1);
    cluster_wait();
    TC(tc2);
    mbar_wait(bar + 8 * B_AF, 0, rg.spin);
    mbar_wait(bar + 8 * B_WF, 0, rg.spin);
    uint32_t om0, om1;
    {
      float acc[108];
      mma_loop<0>(acc, rg, bar, rel, dlo_a, dlo_b, lane, trb, nomid);
      if ((w8 & 3) == 0 && lane == 0) TR(400 + 20 * cw);
      mbar_wait(bar + 8 * B_GREADY, 0, rg.spin);
      const float g0 = __uint_as_float(lds16(sb + G_OFF + 2 * prow) << 16), g1 = __uint_as_float(lds16(sb + G_OFF + 2 * (prow + 16)) << 16);
      om0 = pack_bf16(1.f - g0, 1.f - g0); om1 = pack_bf16(1.f - g1, 1.f - g1);
      const int sr = 16 * w8 + srow;
      const uint32_t sa = sb + R0 + sr * 128, x4 = (uint32_t)(((lane >> 4) ^ (sr & 7)) << 4);
      uint32_t* hn = reinterpret_cast<uint32_t*>(g_H) + (uint32_t)((128 * i + 16 * w8 + (lane >> 2)) * (FF / 2) + 768 + 12 * j + (lane & 3));
#pragma unroll
      for (int g32 = 0; g32 < 7; g32++) {
        uint32_t b[4], v[8];
        ldsm4(b, bias + 64 * g32);
#pragma unroll
        for (int e = 0; e < (g32 < 6 ? 8 : 6); e++) {
          const uint32_t rl = add_relu_bf16x2(pack_bf16(acc[16 * g32 + 2 * e], acc[16 * g32 + 2 * e + 1]), b[e >> 1]);
          v[e] = mul_bf16x2(mul_bf16x2(rl, rl), (e & 1) ? om1 : om0);
        }
        if (g32 < 6) {
#pragma unroll
          for (int e = 0; e < 2; e++) {
            const int g8 = 4 * g32 + 2 * e;
            stmatrix_x4(sa + (g8 >> 3) * 16384 + ((uint32_t)((g8 & 7) << 4) ^ x4), v[4 * e], v[4 * e + 1], v[4 * e + 2], v[4 * e + 3]);
          }
        } else {
#pragma unroll
          for (int e = 0; e < 6; e++) hn[(e & 1) * 8 * (FF / 2) + 4 * (e >> 1)] = v[e];
        }
      }
      fence_async_smem();
      __syncwarp();
      if (lane == 0) mbar_arrive(bar + 8 * B_HDONE);
      if ((w8 & 3) == 0 && lane == 0) TR(400 + 20 * cw + 1);
    }
    uint32_t q[20];
    const uint32_t kplane = sb + R0 + (w8 & 1) * PLANE + roff(16 * (w8 >> 1));
    {
      float acc[120];
      mma_loop<1>(acc, rg, bar, rel, dlo_a, dlo_b, lane, trb + N_H, nomid);
      if ((w8 & 3) == 0 && lane == 0) TR(400 + 20 * cw + 2);
      if (w8 >= 6) {
        const uint32_t tag = lds32(sb + TAG_OFF);
        ulonglong2* hp = g_halo + ((cs * 2 + (w8 & 1)) * 320 + lane);
#pragma unroll
        for (int c = 0; c < 10; c++) {
          const int g8 = c % 5 < 4 ? 8 + 8 * (c / 5) + 2 * (c % 5) : 26 + 2 * (c / 5);
          st_ll2(hp + 32 * c, pack_bf16(acc[4 * g8 + 2], acc[4 * g8 + 3]), pack_bf16(acc[4 * g8 + 6], acc[4 * g8 + 7]), tag);
        }
        if (lane == 0) mbar_arrive(bar + 8 * B_KV);
      }
      mbar_wait(bar + 8 * B_HFREE, 0, rg.spin);
      const uint32_t ka = kplane + roff(8 + srow) + (lane >> 4) * 16;
#pragma unroll
      for (int X = 0; X < 2; X++)
#pragma unroll
        for (int c = 0; c < 5; c++) {
          const int g8 = c < 4 ? 8 + 8 * X + 2 * c : 26 + 2 * X;
          stmatrix_x4(ka + X * 2 * PLANE + c * 32, pack_bf16(acc[4 * g8], acc[4 * g8 + 1]), pack_bf16(acc[4 * g8 + 2], acc[4 * g8 + 3]),
                      pack_bf16(acc[4 * g8 + 4], acc[4 * g8 + 5]), pack_bf16(acc[4 * g8 + 6], acc[4 * g8 + 7]));
        }
#pragma unroll
      for (int c = 0; c < 10; c++) {
        const int g8 = c < 8 ? c : 16 + c;
        q[2 * c] = pack_bf16(acc[4 * g8], acc[4 * g8 + 1]); q[2 * c + 1] = pack_bf16(acc[4 * g8 + 2], acc[4 * g8 + 3]);
      }
      if ((w8 & 3) == 0 && lane == 0) TR(400 + 20 * cw + 3);
    }
    float acc[80];
    mma_loop<2>(acc, rg, bar, rel, dlo_a, dlo_b, lane, trb + N_H + N_QKV, [&]() {
      if ((w8 & 3) == 0 && lane == 0) TR(400 + 20 * cw + 4);
      mbar_wait(bar + 8 * B_HALO, 0, rg.spin);
      asm volatile("bar.sync 1, 256;" ::: "memory");
      if ((w8 & 3) == 0 && lane == 0) TR(400 + 20 * cw + 5);
      const float g0 = __uint_as_float(lds16(sb + G_OFF + 2 * prow) << 16), g1 = __uint_as_float(lds16(sb + G_OFF + 2 * (prow + 16)) << 16);
      attention(q, kplane, lane, i == 0 && w8 < 2, g0, g1);
      asm volatile("bar.sync 1, 256;" ::: "memory");
      const uint32_t oa = sb + R0 + (16 * w8 + srow) * 160 + (lane >> 4) * 16;
#pragma unroll
      for (int c = 0; c < 5; c++) stmatrix_x4(oa + c * 32, q[4 * c], q[4 * c + 1], q[4 * c + 2], q[4 * c + 3]);
      fence_async_smem();
      __syncwarp();
      if (lane == 0) mbar_arrive(bar + 8 * B_ODONE);
      if ((w8 & 3) == 0 && lane == 0) TR(400 + 20 * cw + 6);
    });
    if ((w8 & 3) == 0 && lane == 0) TR(400 + 20 * cw + 7);
    {
      if (kh != 0) { om0 = 0; om1 = 0; }
      const uint32_t st = sb + R0 + w8 * 5120;
      const uint32_t sa = st + srow * 128, x4 = (uint32_t)(((lane >> 4) ^ (srow & 7)) << 4);
      const uint32_t sn = st + 4096 + srow * 64, xn = (uint32_t)(((lane >> 4) ^ ((srow >> 1) & 3)) << 4);
#pragma unroll
      for (int g32 = 0; g32 < 5; g32++) {
        uint32_t b[4], v[8];
        ldsm4(b, bias + 448 + 64 * g32);
#pragma unroll
        for (int e = 0; e < 8; e++) v[e] = fma_bf16x2((e & 1) ? om1 : om0, b[e >> 1], pack_bf16(acc[16 * g32 + 2 * e], acc[16 * g32 + 2 * e + 1]));
#pragma unroll
        for (int e = 0; e < 2; e++) {
          const int g8 = 4 * g32 + 2 * e;
          stmatrix_x4(g8 < 16 ? sa + (g8 >> 3) * 2048 + ((uint32_t)((g8 & 7) << 4) ^ x4) : sn + ((uint32_t)((g8 & 3) << 4) ^ xn), v[4 * e], v[4 * e + 1], v[4 * e + 2], v[4 * e + 3]);
        }
      }
      fence_async_smem();
      fence_async_glob();
      __syncwarp();
      if (elect_one()) {
        const int c2 = w8 & 1, c3 = 4 * i + (w8 >> 1);
        tma_reduce_4d(&p.outw, st, 128 * t, c2, c3);
        tma_reduce_4d(&p.outw, st + 2048, 128 * t + 64, c2, c3);
        tma_reduce_4d(&p.outn, st + 4096, 512 + 32 * t, c2, c3);
        asm volatile("cp.async.bulk.commit_group;" ::: "memory");
        asm volatile("cp.async.bulk.wait_group.read 0;" ::: "memory");
      }
      __syncwarp();
    }
    if ((w8 & 3) == 0 && lane == 0) TR(400 + 20 * cw + 8);
    if (tid == 128) atomicAdd(&g_done, 1u);
  }
}

typedef CUresult (*PFN_encodeTiled)(CUtensorMap*, CUtensorMapDataType, cuuint32_t, void*, const cuuint64_t*, const cuuint64_t*,
                                    const cuuint32_t*, const cuuint32_t*, CUtensorMapInterleave, CUtensorMapSwizzle,
                                    CUtensorMapL2promotion, CUtensorMapFloatOOBfill);

void encode(PFN_encodeTiled fn, CUtensorMap* m, const void* base, int rank, const cuuint64_t* dims, const cuuint64_t* strides,
            const cuuint32_t* box, CUtensorMapSwizzle swz) {
  cuuint32_t es[5] = {1, 1, 1, 1, 1};
  fn(m, CU_TENSOR_MAP_DATA_TYPE_BFLOAT16, rank, const_cast<void*>(base), dims, strides, box, es, CU_TENSOR_MAP_INTERLEAVE_NONE, swz,
     CU_TENSOR_MAP_L2_PROMOTION_L2_128B, CU_TENSOR_MAP_FLOAT_OOB_FILL_NONE);
}
void encode4d(PFN_encodeTiled fn, CUtensorMap* m, const void* base, uint64_t d0, uint64_t d1, uint64_t d2, uint64_t d3, uint64_t s1, uint64_t s2, uint64_t s3,
              uint32_t b0, uint32_t b1, uint32_t b2, uint32_t b3, CUtensorMapSwizzle swz) {
  cuuint64_t dims[4] = {d0, d1, d2, d3}; cuuint64_t st[3] = {s1, s2, s3}; cuuint32_t box[4] = {b0, b1, b2, b3};
  encode(fn, m, base, 4, dims, st, box, swz);
}

}

extern "C" void kernel_launch(void* const* d_in, const int* in_sizes, int n_in, void* d_out, int out_size) {
  static Params prm;
  static void* cached[10] = {};
  static bool attr_done = false;
  bool same = attr_done;
  for (int k = 0; k < 9; k++) same = same && cached[k] == d_in[k];
  same = same && cached[9] == d_out;
  if (!same) {
    void* fnp = nullptr;
    cudaDriverEntryPointQueryResult qr;
    cudaGetDriverEntryPoint("cuTensorMapEncodeTiled", &fnp, cudaEnableDefault, &qr);
    PFN_encodeTiled fn = (PFN_encodeTiled)fnp;
    const __nv_bfloat16* ax = (const __nv_bfloat16*)d_in[0];
    const __nv_bfloat16* wqkv = (const __nv_bfloat16*)d_in[1];
    const __nv_bfloat16* wo = (const __nv_bfloat16*)d_in[2];
    const __nv_bfloat16* w1 = (const __nv_bfloat16*)d_in[4];
    const __nv_bfloat16* w2 = (const __nv_bfloat16*)d_in[6];
    void *hp = nullptr, *op = nullptr;
    cudaGetSymbolAddress(&hp, g_H);
    cudaGetSymbolAddress(&op, g_O);
    const CUtensorMapSwizzle S128 = CU_TENSOR_MAP_SWIZZLE_128B, S64 = CU_TENSOR_MAP_SWIZZLE_64B, S0 = CU_TENSOR_MAP_SWIZZLE_NONE;
    encode4d(fn, &prm.a[0], ax, DM, 16, 2, SEQ / 32, 2 * DM * 2, DM * 2, 32 * DM * 2, 64, 16, 2, 4, S128);
    encode4d(fn, &prm.a[1], hp, FF, 16, 2, SEQ / 32, FF * 2, 16 * FF * 2, 32 * FF * 2, 64, 16, 2, 4, S128);
    encode4d(fn, &prm.a[2], op, DM, 16, 2, SEQ / 32, DM * 2, 16 * DM * 2, 32 * DM * 2, 64, 16, 2, 4, S128);
    encode4d(fn, &prm.hst, hp, FF, 16, 2, SEQ / 32, FF * 2, 16 * FF * 2, 32 * FF * 2, 64, 16, 2, 1, S128);
    encode4d(fn, &prm.ost, op, DM, 16, 2, SEQ / 32, DM * 2, 16 * DM * 2, 32 * DM * 2, 80, 16, 2, 4, S0);
    encode4d(fn, &prm.outw, d_out, DM, 16, 2, SEQ / 32, 2 * DM * 2, DM * 2, 32 * DM * 2, 64, 16, 1, 1, S128);
    encode4d(fn, &prm.outn, d_out, DM, 16, 2, SEQ / 32, 2 * DM * 2, DM * 2, 32 * DM * 2, 32, 16, 1, 1, S64);
    encode4d(fn, &prm.w[0], w1, 64, DM, 3, 8, FF * 2, 128, 384, 64, 32, 3, 1, S128);
    encode4d(fn, &prm.w[1], w1 + 1536, 24, DM, 1, 8, FF * 2, 128, 48, NBOX1, 32, 1, 1, S128);
    encode4d(fn, &prm.w[2], wqkv, 64, DM, 3, 8, 3 * DM * 2, DM * 2, 160, 64, 32, 3, 1, S128);
    encode4d(fn, &prm.w[3], wqkv + 64, 16, DM, 3, 8, 3 * DM * 2, DM * 2, 160, 16, 32, 3, 1, CU_TENSOR_MAP_SWIZZLE_32B);
    encode4d(fn, &prm.w[4], w2, 64, FF, 2, 4, DM * 2, 128, 256, 64, 32, 2, 1, S128);
    encode4d(fn, &prm.w[5], w2 + 512, 32, FF, 1, 4, DM * 2, 128, 64, NBOX2, 32, 1, 1, S128);
    encode4d(fn, &prm.w[6], wo, 64, DM, 2, 4, DM * 2, 128, 256, 64, 32, 2, 1, S128);
    encode4d(fn, &prm.w[7], wo + 512, 32, DM, 1, 4, DM * 2, 128, 64, NBOX2, 32, 1, 1, S128);
    prm.pwqkv = wqkv; prm.pwo = wo; prm.pw2 = w2;
    cudaFuncSetAttribute(fused_kernel, cudaFuncAttributeMaxDynamicSharedMemorySize, SMEM_BYTES);
    for (int k = 0; k < 9; k++) cached[k] = d_in[k];
    cached[9] = d_out;
    attr_done = true;
  }
  cudaLaunchConfig_t cfg = {};
  cfg.gridDim = dim3(NCTA);
  cfg.blockDim = dim3(NTHREADS);
  cfg.dynamicSmemBytes = SMEM_BYTES;
  cfg.stream = cudaStreamPerThread;
  cudaLaunchKernelEx(&cfg, fused_kernel, (const __nv_bfloat16*)d_in[0], (const __nv_bfloat16*)d_in[4], (const __nv_bfloat16*)d_in[5],
                     (const __nv_bfloat16*)d_in[8], (__nv_bfloat16*)d_out, (const __nv_bfloat16*)d_in[7], prm);
}
```

```cpp
#include <cuda_runtime.h>
#include <cuda_bf16.h>
#include <cuda.h>
#include <stdint.h>

namespace {

constexpr int SEQ = 2048, DM = 640, FF = 1728;
constexpr int NCTA = 128;
constexpr int NTHREADS = 384;

constexpr uint32_t PAGE = 16384;
constexpr int NA = 4, NW = 7;
constexpr uint32_t WB = NA * PAGE;
constexpr uint32_t R0 = (NA + NW) * PAGE;
constexpr uint32_t ZERO_OFF = 32768;
constexpr uint32_t PLANE = 72 * 160 + 18 * 16;
constexpr uint32_t BAR_OFF = R0 + 49152;
constexpr uint32_t G_OFF = BAR_OFF + 512;
constexpr uint32_t TAG_OFF = BAR_OFF + 496;
constexpr uint32_t BIAS_OFF = G_OFF + 256;
constexpr uint32_t SMEM_BYTES = BIAS_OFF + 320;
static_assert(SMEM_BYTES <= 232448 && R0 % 1024 == 0 && 4 * PLANE <= 49152, "smem");

enum { B_AF = 0, B_AE = 4, B_WF = 8, B_WE = 15, B_GREADY = 22, B_HFREE = 23, B_HALO = 24, B_ODONE = 25, B_XG = 26, B_KV = 27, B_LV = 28, B_DUMMY = 33, B_HDONE = 34, B_NBAR = 38 };
#define NBOX1 24
#define NBOX2 32
constexpr uint32_t BYTES_W1 = 12288 + NBOX1 * 64, BYTES_W2 = 8192 + NBOX2 * 64;
constexpr int N_H = 20, N_QKV = 20, N_P3 = 37;
#define ATTPOS 8
constexpr int ATT_POS = ATTPOS;
#define WATCH1 2
#define RELMASK 3
#define TAILSPLIT 2
#define G6POS 0
#define HOLD_H 4
#define HOLD_Q 0
#define HOLD_P 7
#define TAILREL 6
#define LEADWG 1
#define PROBE_FIRST
#define HPACE 600
constexpr uint32_t H_PACE = HPACE;

#define OLDEPI
#define LATEARR
#define REG_P 72
#define REG_C 216
template <int V> struct IC { static constexpr int value = V; };
struct Params {
  CUtensorMap w[8];
  CUtensorMap a[3];
  CUtensorMap hst, ost, outw, outn;
  const __nv_bfloat16 *pwqkv, *pwo, *pw2;
};

__device__ __align__(1024) __nv_bfloat16 g_H[SEQ * FF];
__device__ __align__(1024) __nv_bfloat16 g_O[SEQ * DM];
__device__ __align__(128) unsigned long long g_gateLL[SEQ];
__device__ __align__(128) ulonglong2 g_halo[128 * 2 * 10 * 32];
__device__ __align__(128) uint32_t g_flag[16 * 32];
__device__ __align__(128) uint32_t g_done;

#define TR(slot) do {} while (0)
#define TRW(slot) do {} while (0)
__device__ __forceinline__ uint32_t smem_u32(const void* p) { return (uint32_t)__cvta_generic_to_shared(p); }
__device__ __forceinline__ void mbar_init(uint32_t bar, uint32_t cnt) { asm volatile("mbarrier.init.shared::cta.b64 [%0], %1;" ::"r"(bar), "r"(cnt) : "memory"); }
__device__ __forceinline__ void mbar_expect_tx(uint32_t bar, uint32_t bytes) { asm volatile("mbarrier.arrive.expect_tx.shared::cta.b64 _, [%0], %1;" ::"r"(bar), "r"(bytes) : "memory"); }
__device__ __forceinline__ void mbar_arrive(uint32_t bar) { asm volatile("mbarrier.arrive.shared::cta.b64 _, [%0];" ::"r"(bar) : "memory"); }
__device__ __forceinline__ uint32_t mapa(uint32_t addr, uint32_t cta) { uint32_t r; asm volatile("mapa.shared::cluster.u32 %0, %1, %2;" : "=r"(r) : "r"(addr), "r"(cta)); return r; }
__device__ __forceinline__ void mbar_arrive_remote(uint32_t rbar) { asm volatile("mbarrier.arrive.shared::cluster.b64 _, [%0];" ::"r"(rbar) : "memory"); }
#define SPINLOG 13
constexpr uint32_t SPIN_MAX = 1u << SPINLOG;
__device__ __forceinline__ void mbar_wait(uint32_t bar, uint32_t parity, uint32_t& n) {
  asm volatile("{\n.reg .pred p, q;\nLAB_WAIT:\n"
               "mbarrier.try_wait.parity.shared::cta.b64 p, [%1], %2;\n"
               "add.u32 %0, %0, 1;\nsetp.lt.and.u32 q, %0, %3, !p;\n@q bra LAB_WAIT;\n}" : "+r"(n) : "r"(bar), "r"(parity), "n"(SPIN_MAX) : "memory");
}
__device__ __forceinline__ bool elect_one() {
  uint32_t p;
  asm volatile("{\n.reg .pred P;\nelect.sync _|P, 0xffffffff;\nselp.u32 %0, 1, 0, P;\n}" : "=r"(p));
  return p;
}
__device__ __forceinline__ void tma_4d(uint32_t dst, const CUtensorMap* tm, int c0, int c1, int c2, int c3, uint32_t bar) {
  asm volatile("cp.async.bulk.tensor.4d.shared::cluster.global.mbarrier::complete_tx::bytes [%0], [%1, {%3, %4, %5, %6}], [%2];"
               ::"r"(dst), "l"(tm), "r"(bar), "r"(c0), "r"(c1), "r"(c2), "r"(c3) : "memory");
}
__device__ __forceinline__ void tma_4d_mc(uint32_t dst, const CUtensorMap* tm, int c0, int c1, int c2, int c3, uint32_t bar) {
  asm volatile("cp.async.bulk.tensor.4d.shared::cluster.global.mbarrier::complete_tx::bytes.multicast::cluster [%0], [%1, {%3, %4, %5, %6}], [%2], %7;"
               ::"r"(dst), "l"(tm), "r"(bar), "r"(c0), "r"(c1), "r"(c2), "r"(c3), "h"((uint16_t)3) : "memory");
}
__device__ __forceinline__ void tma_store_4d(const CUtensorMap* tm, uint32_t src, int c0, int c1, int c2, int c3) {
  asm volatile("cp.async.bulk.tensor.4d.global.shared::cta.bulk_group [%0, {%2, %3, %4, %5}], [%1];" ::"l"(tm), "r"(src), "r"(c0), "r"(c1), "r"(c2), "r"(c3) : "memory");
}
__device__ __forceinline__ void tma_reduce_4d(const CUtensorMap* tm, uint32_t src, int c0, int c2, int c3) {
  asm volatile("cp.reduce.async.bulk.tensor.4d.global.shared::cta.add.bulk_group [%0, {%2, %5, %3, %4}], [%1];" ::"l"(tm), "r"(src), "r"(c0), "r"(c2), "r"(c3), "r"(0) : "memory");
}
__device__ __forceinline__ void bulk_load(uint32_t dst, const void* src, uint32_t bytes, uint32_t bar) {
  asm volatile("cp.async.bulk.shared::cluster.global.mbarrier::complete_tx::bytes [%0], [%1], %2, [%3];" ::"r"(dst), "l"(src), "r"(bytes), "r"(bar) : "memory");
}
__device__ __forceinline__ void bulk_store(void* dst, uint32_t src, uint32_t bytes) {
  asm volatile("cp.async.bulk.global.shared::cta.bulk_group [%0], [%1], %2;" ::"l"(dst), "r"(src), "r"(bytes) : "memory");
}
__device__ __forceinline__ void l2_prefetch(const void* src, uint32_t bytes) {
  asm volatile("cp.async.bulk.prefetch.L2.global [%0], %1;" ::"l"(src), "r"(bytes) : "memory");
}
__device__ __forceinline__ void cp_async16(uint32_t dst, const void* src) { asm volatile("cp.async.cg.shared.global [%0], [%1], 16;" ::"r"(dst), "l"(src) : "memory"); }
__device__ __forceinline__ void prefetch_tmap(const CUtensorMap* tm) { asm volatile("prefetch.tensormap [%0];" ::"l"(tm) : "memory"); }
__device__ __forceinline__ void fence_async_smem() { asm volatile("fence.proxy.async.shared::cta;" ::: "memory"); }
__device__ __forceinline__ void fence_async_glob() { asm volatile("fence.proxy.async.global;" ::: "memory"); }
__device__ __forceinline__ void wg_fence() { asm volatile("wgmma.fence.sync.aligned;" ::: "memory"); }
__device__ __forceinline__ void wg_commit() { asm volatile("wgmma.commit_group.sync.aligned;" ::: "memory"); }
template <int N> __device__ __forceinline__ void wg_wait() { asm volatile("wgmma.wait_group.sync.aligned %0;" ::"n"(N) : "memory"); }
__device__ __forceinline__ uint64_t make_desc(uint32_t addr, uint32_t lbo, uint32_t sbo, uint32_t swz  ) {
  return (uint64_t)((addr & 0x3FFFF) >> 4) | ((uint64_t)(lbo >> 4) << 16) | ((uint64_t)(sbo >> 4) << 32) | ((uint64_t)swz << 62);
}
__device__ __forceinline__ void stmatrix_x4(uint32_t addr, uint32_t a, uint32_t b, uint32_t c, uint32_t d) {
  asm volatile("stmatrix.sync.aligned.m8n8.x4.shared.b16 [%0], {%1, %2, %3, %4};" ::"r"(addr), "r"(a), "r"(b), "r"(c), "r"(d) : "memory");
}
__device__ __forceinline__ void ldsm4(uint32_t* d, uint32_t addr) {
  asm volatile("ldmatrix.sync.aligned.m8n8.x4.shared.b16 {%0, %1, %2, %3}, [%4];" : "=r"(d[0]), "=r"(d[1]), "=r"(d[2]), "=r"(d[3]) : "r"(addr) : "memory");
}
__device__ __forceinline__ void ldsm4t(uint32_t* d, uint32_t addr) {
  asm volatile("ldmatrix.sync.aligned.m8n8.x4.trans.shared.b16 {%0, %1, %2, %3}, [%4];" : "=r"(d[0]), "=r"(d[1]), "=r"(d[2]), "=r"(d[3]) : "r"(addr) : "memory");
}
__device__ __forceinline__ void mma16z(float* d, uint32_t a0, uint32_t a1, uint32_t a2, uint32_t a3, uint32_t b0, uint32_t b1) {
  asm volatile("mma.sync.aligned.m16n8k16.row.col.f32.bf16.bf16.f32 {%0, %1, %2, %3}, {%4, %5, %6, %7}, {%8, %9}, {%10, %10, %10, %10};"
               : "=f"(d[0]), "=f"(d[1]), "=f"(d[2]), "=f"(d[3]) : "r"(a0), "r"(a1), "r"(a2), "r"(a3), "r"(b0), "r"(b1), "f"(0.f));
}
__device__ __forceinline__ void mma16(float* d, uint32_t a0, uint32_t a1, uint32_t a2, uint32_t a3, uint32_t b0, uint32_t b1) {
  asm volatile("mma.sync.aligned.m16n8k16.row.col.f32.bf16.bf16.f32 {%0, %1, %2, %3}, {%4, %5, %6, %7}, {%8, %9}, {%0, %1, %2, %3};"
               : "+f"(d[0]), "+f"(d[1]), "+f"(d[2]), "+f"(d[3]) : "r"(a0), "r"(a1), "r"(a2), "r"(a3), "r"(b0), "r"(b1));
}
__device__ __forceinline__ void mma8z(float* d, uint32_t a0, uint32_t a1, uint32_t b0) {
  asm volatile("mma.sync.aligned.m16n8k8.row.col.f32.bf16.bf16.f32 {%0, %1, %2, %3}, {%4, %5}, {%6}, {%7, %7, %7, %7};"
               : "=f"(d[0]), "=f"(d[1]), "=f"(d[2]), "=f"(d[3]) : "r"(a0), "r"(a1), "r"(b0), "f"(0.f));
}
__device__ __forceinline__ void mma8(float* d, uint32_t a0, uint32_t a1, uint32_t b0) {
  asm volatile("mma.sync.aligned.m16n8k8.row.col.f32.bf16.bf16.f32 {%0, %1, %2, %3}, {%4, %5}, {%6}, {%0, %1, %2, %3};"
               : "+f"(d[0]), "+f"(d[1]), "+f"(d[2]), "+f"(d[3]) : "r"(a0), "r"(a1), "r"(b0));
}
__device__ __forceinline__ uint32_t pack_bf16(float lo, float hi) {
  uint32_t r; asm("cvt.rn.bf16x2.f32 %0, %1, %2;" : "=r"(r) : "f"(hi), "f"(lo)); return r;
}
__device__ __forceinline__ uint32_t pack_bf16_relu(float lo, float hi) {
  uint32_t r; asm("cvt.rn.relu.bf16x2.f32 %0, %1, %2;" : "=r"(r) : "f"(hi), "f"(lo)); return r;
}
__device__ __forceinline__ uint32_t add_relu_bf16x2(uint32_t a, uint32_t b) {
  uint32_t r; asm("fma.rn.relu.bf16x2 %0, %1, %2, %3;" : "=r"(r) : "r"(a), "r"(0x3f803f80u), "r"(b)); return r;
}
__device__ __forceinline__ uint32_t fma_bf16x2(uint32_t a, uint32_t b, uint32_t c) {
  uint32_t r; asm("fma.rn.bf16x2 %0, %1, %2, %3;" : "=r"(r) : "r"(a), "r"(b), "r"(c)); return r;
}
__device__ __forceinline__ void prefetch_l2(const void* p) { asm volatile("prefetch.global.L2 [%0];" ::"l"(p)); }
__device__ __forceinline__ uint32_t mul_bf16x2(uint32_t a, uint32_t b) {
  uint32_t r; asm("mul.rn.bf16x2 %0, %1, %2;" : "=r"(r) : "r"(a), "r"(b)); return r;
}
__device__ __forceinline__ float bf_lo(uint32_t w) { return __uint_as_float(w << 16); }
__device__ __forceinline__ float bf_hi(uint32_t w) { return __uint_as_float(w & 0xffff0000u); }
__device__ __forceinline__ uint32_t lds16(uint32_t a) { uint16_t v; asm volatile("ld.shared.u16 %0, [%1];" : "=h"(v) : "r"(a)); return v; }
__device__ __forceinline__ void sts16(uint32_t a, uint16_t v) { asm volatile("st.shared.u16 [%0], %1;" ::"r"(a), "h"(v) : "memory"); }
__device__ __forceinline__ uint32_t ld_acquire(const uint32_t* p) { uint32_t v; asm volatile("ld.acquire.gpu.global.u32 %0, [%1];" : "=r"(v) : "l"(p) : "memory"); return v; }
__device__ __forceinline__ void st_flag(uint32_t* p, uint32_t v) { asm volatile("st.release.gpu.global.u32 [%0], %1;" ::"l"(p), "r"(v) : "memory"); }
__device__ __forceinline__ uint32_t ld_relaxed(const uint32_t* p) { uint32_t v; asm volatile("ld.relaxed.gpu.global.u32 %0, [%1];" : "=r"(v) : "l"(p) : "memory"); return v; }
__device__ __forceinline__ void st_relaxed(uint32_t* p, uint32_t v) { asm volatile("st.relaxed.gpu.global.u32 [%0], %1;" ::"l"(p), "r"(v) : "memory"); }
__device__ __forceinline__ float ex2(float x) { float r; asm("ex2.approx.ftz.f32 %0, %1;" : "=f"(r) : "f"(x)); return r; }
__device__ __forceinline__ float rcp(float x) { float r; asm("rcp.approx.ftz.f32 %0, %1;" : "=f"(r) : "f"(x)); return r; }
__device__ __forceinline__ uint64_t ld_ll(const unsigned long long* p) { uint64_t v; asm volatile("ld.relaxed.gpu.global.b64 %0, [%1];" : "=l"(v) : "l"(p) : "memory"); return v; }
__device__ __forceinline__ void st_ll(unsigned long long* p, uint32_t x, uint32_t tag) {
  asm volatile("st.relaxed.gpu.global.b64 [%0], %1;" ::"l"(p), "l"(((uint64_t)tag << 32) | x) : "memory");
}
__device__ __forceinline__ uint4 ld_acquire4(const uint32_t* p) {
  uint4 v; asm volatile("ld.acquire.gpu.global.v4.u32 {%0, %1, %2, %3}, [%4];" : "=r"(v.x), "=r"(v.y), "=r"(v.z), "=r"(v.w) : "l"(p) : "memory"); return v;
}
__device__ __forceinline__ ulonglong2 ld_ll2(const ulonglong2* p) {
  ulonglong2 v; asm volatile("ld.relaxed.gpu.global.v2.b64 {%0, %1}, [%2];" : "=l"(v.x), "=l"(v.y) : "l"(p) : "memory"); return v;
}
__device__ __forceinline__ void st_ll2(ulonglong2* p, uint32_t x, uint32_t y, uint32_t tag) {
  asm volatile("st.relaxed.gpu.global.v2.b64 [%0], {%1, %2};" ::"l"(p), "l"(((uint64_t)tag << 32) | x), "l"(((uint64_t)tag << 32) | y) : "memory");
}
__device__ __forceinline__ void sts32(uint32_t a, uint32_t x) { asm volatile("st.shared.u32 [%0], %1;" ::"r"(a), "r"(x) : "memory"); }
__device__ __forceinline__ uint32_t lds32(uint32_t a) { uint32_t v; asm volatile("ld.shared.u32 %0, [%1];" : "=r"(v) : "r"(a) : "memory"); return v; }
__device__ __forceinline__ void sts64(uint32_t a, uint32_t x, uint32_t y) { asm volatile("st.shared.v2.u32 [%0], {%1, %2};" ::"r"(a), "r"(x), "r"(y) : "memory"); }
__device__ __forceinline__ void sts128(uint32_t a, uint4 v) { asm volatile("st.shared.v4.u32 [%0], {%1, %2, %3, %4};" ::"r"(a), "r"(v.x), "r"(v.y), "r"(v.z), "r"(v.w) : "memory"); }
__device__ __forceinline__ uint4 lds128(uint32_t a) { uint4 v; asm volatile("ld.shared.v4.u32 {%0, %1, %2, %3}, [%4];" : "=r"(v.x), "=r"(v.y), "=r"(v.z), "=r"(v.w) : "r"(a) : "memory"); return v; }
__device__ __forceinline__ uint2 lds64(uint32_t a) { uint2 v; asm volatile("ld.shared.v2.u32 {%0, %1}, [%2];" : "=r"(v.x), "=r"(v.y) : "r"(a) : "memory"); return v; }
__device__ __forceinline__ void fence_gpu() { asm volatile("fence.acq_rel.gpu;" ::: "memory"); }
__device__ __forceinline__ void cluster_arrive() { asm volatile("barrier.cluster.arrive.relaxed.aligned;" ::: "memory"); }
__device__ __forceinline__ void cluster_wait() { asm volatile("barrier.cluster.wait.aligned;" ::: "memory"); }
__device__ __forceinline__ uint32_t roff(int r) { return 160 * r + 16 * (r >> 2); }

template <int N> __device__ __forceinline__ void fence_regs(float* a) {
#pragma unroll
  for (int k = 0; k < N; k++) asm volatile("" : "+f"(a[k])::"memory");
}

__device__ __forceinline__ void iter_h_e(float* d, uint64_t da, uint64_t db, uint32_t wbar, uint32_t wpar, int sc) {
  asm volatile(
    "{\n"
    ".reg .pred s, t;\n"
    "mbarrier.test_wait.parity.shared::cta.b64 pw0, [%112], %113;\n"
    "setp.eq.b32 t, 0, 0;\n"
    "setp.ne.b32 s, %114, 0;\n"
    "wgmma.fence.sync.aligned;\n"
    "wgmma.mma_async.sync.aligned.m64n216k16.f32.bf16.bf16 {%0, %1, %2, %3, %4, %5, %6, %7, %8, %9, %10, %11, %12, %13, %14, %15, %16, %17, %18, %19, %20, %21, %22, %23, %24, %25, %26, %27, %28, %29, %30, %31, %32, %33, %34, %35, %36, %37, %38, %39, %40, %41, %42, %43, %44, %45, %46, %47, %48, %49, %50, %51, %52, %53, %54, %55, %56, %57, %58, %59, %60, %61, %62, %63, %64, %65, %66, %67, %68, %69, %70, %71, %72, %73, %74, %75, %76, %77, %78, %79, %80, %81, %82, %83, %84, %85, %86, %87, %88, %89, %90, %91, %92, %93, %94, %95, %96, %97, %98, %99, %100, %101, %102, %103, %104, %105, %106, %107}, %108, %110, s, 1, 1, 0, 1;\n"
    "wgmma.mma_async.sync.aligned.m64n216k16.f32.bf16.bf16 {%0, %1, %2, %3, %4, %5, %6, %7, %8, %9, %10, %11, %12, %13, %14, %15, %16, %17, %18, %19, %20, %21, %22, %23, %24, %25, %26, %27, %28, %29, %30, %31, %32, %33, %34, %35, %36, %37, %38, %39, %40, %41, %42, %43, %44, %45, %46, %47, %48, %49, %50, %51, %52, %53, %54, %55, %56, %57, %58, %59, %60, %61, %62, %63, %64, %65, %66, %67, %68, %69, %70, %71, %72, %73, %74, %75, %76, %77, %78, %79, %80, %81, %82, %83, %84, %85, %86, %87, %88, %89, %90, %91, %92, %93, %94, %95, %96, %97, %98, %99, %100, %101, %102, %103, %104, %105, %106, %107}, %109, %111, t, 1, 1, 0, 1;\n"
    "wgmma.commit_group.sync.aligned;\n"
    "}\n"
    : "+f"(d[0]), "+f"(d[1]), "+f"(d[2]), "+f"(d[3]), "+f"(d[4]), "+f"(d[5]), "+f"(d[6]), "+f"(d[7]), "+f"(d[8]), "+f"(d[9]), "+f"(d[10]), "+f"(d[11]), "+f"(d[12]), "+f"(d[13]), "+f"(d[14]), "+f"(d[15]), "+f"(d[16]), "+f"(d[17]), "+f"(d[18]), "+f"(d[19]), "+f"(d[20]), "+f"(d[21]), "+f"(d[22]), "+f"(d[23]), "+f"(d[24]), "+f"(d[25]), "+f"(d[26]), "+f"(d[27]), "+f"(d[28]), "+f"(d[29]), "+f"(d[30]), "+f"(d[31]), "+f"(d[32]), "+f"(d[33]), "+f"(d[34]), "+f"(d[35]), "+f"(d[36]), "+f"(d[37]), "+f"(d[38]), "+f"(d[39]), "+f"(d[40]), "+f"(d[41]), "+f"(d[42]), "+f"(d[43]), "+f"(d[44]), "+f"(d[45]), "+f"(d[46]), "+f"(d[47]), "+f"(d[48]), "+f"(d[49]), "+f"(d[50]), "+f"(d[51]), "+f"(d[52]), "+f"(d[53]), "+f"(d[54]), "+f"(d[55]), "+f"(d[56]), "+f"(d[57]), "+f"(d[58]), "+f"(d[59]), "+f"(d[60]), "+f"(d[61]), "+f"(d[62]), "+f"(d[63]), "+f"(d[64]), "+f"(d[65]), "+f"(d[66]), "+f"(d[67]), "+f"(d[68]), "+f"(d[69]), "+f"(d[70]), "+f"(d[71]), "+f"(d[72]), "+f"(d[73]), "+f"(d[74]), "+f"(d[75]), "+f"(d[76]), "+f"(d[77]), "+f"(d[78]), "+f"(d[79]), "+f"(d[80]), "+f"(d[81]), "+f"(d[82]), "+f"(d[83]), "+f"(d[84]), "+f"(d[85]), "+f"(d[86]), "+f"(d[87]), "+f"(d[88]), "+f"(d[89]), "+f"(d[90]), "+f"(d[91]), "+f"(d[92]), "+f"(d[93]), "+f"(d[94]), "+f"(d[95]), "+f"(d[96]), "+f"(d[97]), "+f"(d[98]), "+f"(d[99]), "+f"(d[100]), "+f"(d[101]), "+f"(d[102]), "+f"(d[103]), "+f"(d[104]), "+f"(d[105]), "+f"(d[106]), "+f"(d[107])
    : "l"(da), "l"(da + 2), "l"(db), "l"(db + 128), "r"(wbar), "r"(wpar), "r"(sc)
    : "memory");
}
__device__ __forceinline__ void iter_q_e(float* d, uint64_t da, uint64_t db, uint64_t dn, uint32_t wbar, uint32_t wpar, int sc) {
  asm volatile(
    "{\n"
    ".reg .pred s, t;\n"
    "mbarrier.test_wait.parity.shared::cta.b64 pw1, [%126], %127;\n"
    "setp.eq.b32 t, 0, 0;\n"
    "setp.ne.b32 s, %128, 0;\n"
    "wgmma.fence.sync.aligned;\n"
    "wgmma.mma_async.sync.aligned.m64n192k16.f32.bf16.bf16 {%0, %1, %2, %3, %4, %5, %6, %7, %8, %9, %10, %11, %12, %13, %14, %15, %16, %17, %18, %19, %20, %21, %22, %23, %24, %25, %26, %27, %28, %29, %30, %31, %32, %33, %34, %35, %36, %37, %38, %39, %40, %41, %42, %43, %44, %45, %46, %47, %48, %49, %50, %51, %52, %53, %54, %55, %56, %57, %58, %59, %60, %61, %62, %63, %64, %65, %66, %67, %68, %69, %70, %71, %72, %73, %74, %75, %76, %77, %78, %79, %80, %81, %82, %83, %84, %85, %86, %87, %88, %89, %90, %91, %92, %93, %94, %95}, %120, %122, s, 1, 1, 0, 1;\n"
    "wgmma.mma_async.sync.aligned.m64n48k16.f32.bf16.bf16 {%96, %97, %98, %99, %100, %101, %102, %103, %104, %105, %106, %107, %108, %109, %110, %111, %112, %113, %114, %115, %116, %117, %118, %119}, %120, %124, s, 1, 1, 0, 1;\n"
    "wgmma.mma_async.sync.aligned.m64n192k16.f32.bf16.bf16 {%0, %1, %2, %3, %4, %5, %6, %7, %8, %9, %10, %11, %12, %13, %14, %15, %16, %17, %18, %19, %20, %21, %22, %23, %24, %25, %26, %27, %28, %29, %30, %31, %32, %33, %34, %35, %36, %37, %38, %39, %40, %41, %42, %43, %44, %45, %46, %47, %48, %49, %50, %51, %52, %53, %54, %55, %56, %57, %58, %59, %60, %61, %62, %63, %64, %65, %66, %67, %68, %69, %70, %71, %72, %73, %74, %75, %76, %77, %78, %79, %80, %81, %82, %83, %84, %85, %86, %87, %88, %89, %90, %91, %92, %93, %94, %95}, %121, %123, t, 1, 1, 0, 1;\n"
    "wgmma.mma_async.sync.aligned.m64n48k16.f32.bf16.bf16 {%96, %97, %98, %99, %100, %101, %102, %103, %104, %105, %106, %107, %108, %109, %110, %111, %112, %113, %114, %115, %116, %117, %118, %119}, %121, %125, t, 1, 1, 0, 1;\n"
    "wgmma.commit_group.sync.aligned;\n"
    "}\n"
    : "+f"(d[0]), "+f"(d[1]), "+f"(d[2]), "+f"(d[3]), "+f"(d[4]), "+f"(d[5]), "+f"(d[6]), "+f"(d[7]), "+f"(d[8]), "+f"(d[9]), "+f"(d[10]), "+f"(d[11]), "+f"(d[12]), "+f"(d[13]), "+f"(d[14]), "+f"(d[15]), "+f"(d[16]), "+f"(d[17]), "+f"(d[18]), "+f"(d[19]), "+f"(d[20]), "+f"(d[21]), "+f"(d[22]), "+f"(d[23]), "+f"(d[24]), "+f"(d[25]), "+f"(d[26]), "+f"(d[27]), "+f"(d[28]), "+f"(d[29]), "+f"(d[30]), "+f"(d[31]), "+f"(d[32]), "+f"(d[33]), "+f"(d[34]), "+f"(d[35]), "+f"(d[36]), "+f"(d[37]), "+f"(d[38]), "+f"(d[39]), "+f"(d[40]), "+f"(d[41]), "+f"(d[42]), "+f"(d[43]), "+f"(d[44]), "+f"(d[45]), "+f"(d[46]), "+f"(d[47]), "+f"(d[48]), "+f"(d[49]), "+f"(d[50]), "+f"(d[51]), "+f"(d[52]), "+f"(d[53]), "+f"(d[54]), "+f"(d[55]), "+f"(d[56]), "+f"(d[57]), "+f"(d[58]), "+f"(d[59]), "+f"(d[60]), "+f"(d[61]), "+f"(d[62]), "+f"(d[63]), "+f"(d[64]), "+f"(d[65]), "+f"(d[66]), "+f"(d[67]), "+f"(d[68]), "+f"(d[69]), "+f"(d[70]), "+f"(d[71]), "+f"(d[72]), "+f"(d[73]), "+f"(d[74]), "+f"(d[75]), "+f"(d[76]), "+f"(d[77]), "+f"(d[78]), "+f"(d[79]), "+f"(d[80]), "+f"(d[81]), "+f"(d[82]), "+f"(d[83]), "+f"(d[84]), "+f"(d[85]), "+f"(d[86]), "+f"(d[87]), "+f"(d[88]), "+f"(d[89]), "+f"(d[90]), "+f"(d[91]), "+f"(d[92]), "+f"(d[93]), "+f"(d[94]), "+f"(d[95]), "+f"(d[96]), "+f"(d[97]), "+f"(d[98]), "+f"(d[99]), "+f"(d[100]), "+f"(d[101]), "+f"(d[102]), "+f"(d[103]), "+f"(d[104]), "+f"(d[105]), "+f"(d[106]), "+f"(d[107]), "+f"(d[108]), "+f"(d[109]), "+f"(d[110]), "+f"(d[111]), "+f"(d[112]), "+f"(d[113]), "+f"(d[114]), "+f"(d[115]), "+f"(d[116]), "+f"(d[117]), "+f"(d[118]), "+f"(d[119])
    : "l"(da), "l"(da + 2), "l"(db), "l"(db + 128), "l"(dn), "l"(dn + 32), "r"(wbar), "r"(wpar), "r"(sc)
    : "memory");
}
__device__ __forceinline__ void iter_p_e(float* d, uint64_t da, uint64_t db, uint32_t wbar, uint32_t wpar, int sc) {
  asm volatile(
    "{\n"
    ".reg .pred s, t;\n"
    "mbarrier.test_wait.parity.shared::cta.b64 pw2, [%84], %85;\n"
    "setp.eq.b32 t, 0, 0;\n"
    "setp.ne.b32 s, %86, 0;\n"
    "wgmma.fence.sync.aligned;\n"
    "wgmma.mma_async.sync.aligned.m64n160k16.f32.bf16.bf16 {%0, %1, %2, %3, %4, %5, %6, %7, %8, %9, %10, %11, %12, %13, %14, %15, %16, %17, %18, %19, %20, %21, %22, %23, %24, %25, %26, %27, %28, %29, %30, %31, %32, %33, %34, %35, %36, %37, %38, %39, %40, %41, %42, %43, %44, %45, %46, %47, %48, %49, %50, %51, %52, %53, %54, %55, %56, %57, %58, %59, %60, %61, %62, %63, %64, %65, %66, %67, %68, %69, %70, %71, %72, %73, %74, %75, %76, %77, %78, %79}, %80, %82, s, 1, 1, 0, 1;\n"
    "wgmma.mma_async.sync.aligned.m64n160k16.f32.bf16.bf16 {%0, %1, %2, %3, %4, %5, %6, %7, %8, %9, %10, %11, %12, %13, %14, %15, %16, %17, %18, %19, %20, %21, %22, %23, %24, %25, %26, %27, %28, %29, %30, %31, %32, %33, %34, %35, %36, %37, %38, %39, %40, %41, %42, %43, %44, %45, %46, %47, %48, %49, %50, %51, %52, %53, %54, %55, %56, %57, %58, %59, %60, %61, %62, %63, %64, %65, %66, %67, %68, %69, %70, %71, %72, %73, %74, %75, %76, %77, %78, %79}, %81, %83, t, 1, 1, 0, 1;\n"
    "wgmma.commit_group.sync.aligned;\n"
    "}\n"
    : "+f"(d[0]), "+f"(d[1]), "+f"(d[2]), "+f"(d[3]), "+f"(d[4]), "+f"(d[5]), "+f"(d[6]), "+f"(d[7]), "+f"(d[8]), "+f"(d[9]), "+f"(d[10]), "+f"(d[11]), "+f"(d[12]), "+f"(d[13]), "+f"(d[14]), "+f"(d[15]), "+f"(d[16]), "+f"(d[17]), "+f"(d[18]), "+f"(d[19]), "+f"(d[20]), "+f"(d[21]), "+f"(d[22]), "+f"(d[23]), "+f"(d[24]), "+f"(d[25]), "+f"(d[26]), "+f"(d[27]), "+f"(d[28]), "+f"(d[29]), "+f"(d[30]), "+f"(d[31]), "+f"(d[32]), "+f"(d[33]), "+f"(d[34]), "+f"(d[35]), "+f"(d[36]), "+f"(d[37]), "+f"(d[38]), "+f"(d[39]), "+f"(d[40]), "+f"(d[41]), "+f"(d[42]), "+f"(d[43]), "+f"(d[44]), "+f"(d[45]), "+f"(d[46]), "+f"(d[47]), "+f"(d[48]), "+f"(d[49]), "+f"(d[50]), "+f"(d[51]), "+f"(d[52]), "+f"(d[53]), "+f"(d[54]), "+f"(d[55]), "+f"(d[56]), "+f"(d[57]), "+f"(d[58]), "+f"(d[59]), "+f"(d[60]), "+f"(d[61]), "+f"(d[62]), "+f"(d[63]), "+f"(d[64]), "+f"(d[65]), "+f"(d[66]), "+f"(d[67]), "+f"(d[68]), "+f"(d[69]), "+f"(d[70]), "+f"(d[71]), "+f"(d[72]), "+f"(d[73]), "+f"(d[74]), "+f"(d[75]), "+f"(d[76]), "+f"(d[77]), "+f"(d[78]), "+f"(d[79])
    : "l"(da), "l"(da + 2), "l"(db), "l"(db + 128), "r"(wbar), "r"(wpar), "r"(sc)
    : "memory");
}
__device__ __forceinline__ void iter_h_o(float* d, uint64_t da, uint64_t db, uint32_t wbar, uint32_t wpar, uint32_t abar, uint32_t apar) {
  asm volatile(
    "{\n"
    ".reg .pred s, t;\n"
    "mbarrier.test_wait.parity.shared::cta.b64 pw0, [%112], %113;\n"
    "mbarrier.test_wait.parity.shared::cta.b64 pa0, [%114], %115;\n"
    "setp.eq.b32 t, 0, 0;\n"
    "wgmma.fence.sync.aligned;\n"
    "wgmma.mma_async.sync.aligned.m64n216k16.f32.bf16.bf16 {%0, %1, %2, %3, %4, %5, %6, %7, %8, %9, %10, %11, %12, %13, %14, %15, %16, %17, %18, %19, %20, %21, %22, %23, %24, %25, %26, %27, %28, %29, %30, %31, %32, %33, %34, %35, %36, %37, %38, %39, %40, %41, %42, %43, %44, %45, %46, %47, %48, %49, %50, %51, %52, %53, %54, %55, %56, %57, %58, %59, %60, %61, %62, %63, %64, %65, %66, %67, %68, %69, %70, %71, %72, %73, %74, %75, %76, %77, %78, %79, %80, %81, %82, %83, %84, %85, %86, %87, %88, %89, %90, %91, %92, %93, %94, %95, %96, %97, %98, %99, %100, %101, %102, %103, %104, %105, %106, %107}, %108, %110, t, 1, 1, 0, 1;\n"
    "wgmma.mma_async.sync.aligned.m64n216k16.f32.bf16.bf16 {%0, %1, %2, %3, %4, %5, %6, %7, %8, %9, %10, %11, %12, %13, %14, %15, %16, %17, %18, %19, %20, %21, %22, %23, %24, %25, %26, %27, %28, %29, %30, %31, %32, %33, %34, %35, %36, %37, %38, %39, %40, %41, %42, %43, %44, %45, %46, %47, %48, %49, %50, %51, %52, %53, %54, %55, %56, %57, %58, %59, %60, %61, %62, %63, %64, %65, %66, %67, %68, %69, %70, %71, %72, %73, %74, %75, %76, %77, %78, %79, %80, %81, %82, %83, %84, %85, %86, %87, %88, %89, %90, %91, %92, %93, %94, %95, %96, %97, %98, %99, %100, %101, %102, %103, %104, %105, %106, %107}, %109, %111, t, 1, 1, 0, 1;\n"
    "wgmma.commit_group.sync.aligned;\n"
    "}\n"
    : "+f"(d[0]), "+f"(d[1]), "+f"(d[2]), "+f"(d[3]), "+f"(d[4]), "+f"(d[5]), "+f"(d[6]), "+f"(d[7]), "+f"(d[8]), "+f"(d[9]), "+f"(d[10]), "+f"(d[11]), "+f"(d[12]), "+f"(d[13]), "+f"(d[14]), "+f"(d[15]), "+f"(d[16]), "+f"(d[17]), "+f"(d[18]), "+f"(d[19]), "+f"(d[20]), "+f"(d[21]), "+f"(d[22]), "+f"(d[23]), "+f"(d[24]), "+f"(d[25]), "+f"(d[26]), "+f"(d[27]), "+f"(d[28]), "+f"(d[29]), "+f"(d[30]), "+f"(d[31]), "+f"(d[32]), "+f"(d[33]), "+f"(d[34]), "+f"(d[35]), "+f"(d[36]), "+f"(d[37]), "+f"(d[38]), "+f"(d[39]), "+f"(d[40]), "+f"(d[41]), "+f"(d[42]), "+f"(d[43]), "+f"(d[44]), "+f"(d[45]), "+f"(d[46]), "+f"(d[47]), "+f"(d[48]), "+f"(d[49]), "+f"(d[50]), "+f"(d[51]), "+f"(d[52]), "+f"(d[53]), "+f"(d[54]), "+f"(d[55]), "+f"(d[56]), "+f"(d[57]), "+f"(d[58]), "+f"(d[59]), "+f"(d[60]), "+f"(d[61]), "+f"(d[62]), "+f"(d[63]), "+f"(d[64]), "+f"(d[65]), "+f"(d[66]), "+f"(d[67]), "+f"(d[68]), "+f"(d[69]), "+f"(d[70]), "+f"(d[71]), "+f"(d[72]), "+f"(d[73]), "+f"(d[74]), "+f"(d[75]), "+f"(d[76]), "+f"(d[77]), "+f"(d[78]), "+f"(d[79]), "+f"(d[80]), "+f"(d[81]), "+f"(d[82]), "+f"(d[83]), "+f"(d[84]), "+f"(d[85]), "+f"(d[86]), "+f"(d[87]), "+f"(d[88]), "+f"(d[89]), "+f"(d[90]), "+f"(d[91]), "+f"(d[92]), "+f"(d[93]), "+f"(d[94]), "+f"(d[95]), "+f"(d[96]), "+f"(d[97]), "+f"(d[98]), "+f"(d[99]), "+f"(d[100]), "+f"(d[101]), "+f"(d[102]), "+f"(d[103]), "+f"(d[104]), "+f"(d[105]), "+f"(d[106]), "+f"(d[107])
    : "l"(da), "l"(da + 2), "l"(db), "l"(db + 128), "r"(wbar), "r"(wpar), "r"(abar), "r"(apar)
    : "memory");
}
__device__ __forceinline__ void iter_q_o(float* d, uint64_t da, uint64_t db, uint64_t dn, uint32_t wbar, uint32_t wpar, uint32_t abar, uint32_t apar) {
  asm volatile(
    "{\n"
    ".reg .pred s, t;\n"
    "mbarrier.test_wait.parity.shared::cta.b64 pw1, [%126], %127;\n"
    "mbarrier.test_wait.parity.shared::cta.b64 pa1, [%128], %129;\n"
    "setp.eq.b32 t, 0, 0;\n"
    "wgmma.fence.sync.aligned;\n"
    "wgmma.mma_async.sync.aligned.m64n192k16.f32.bf16.bf16 {%0, %1, %2, %3, %4, %5, %6, %7, %8, %9, %10, %11, %12, %13, %14, %15, %16, %17, %18, %19, %20, %21, %22, %23, %24, %25, %26, %27, %28, %29, %30, %31, %32, %33, %34, %35, %36, %37, %38, %39, %40, %41, %42, %43, %44, %45, %46, %47, %48, %49, %50, %51, %52, %53, %54, %55, %56, %57, %58, %59, %60, %61, %62, %63, %64, %65, %66, %67, %68, %69, %70, %71, %72, %73, %74, %75, %76, %77, %78, %79, %80, %81, %82, %83, %84, %85, %86, %87, %88, %89, %90, %91, %92, %93, %94, %95}, %120, %122, t, 1, 1, 0, 1;\n"
    "wgmma.mma_async.sync.aligned.m64n48k16.f32.bf16.bf16 {%96, %97, %98, %99, %100, %101, %102, %103, %104, %105, %106, %107, %108, %109, %110, %111, %112, %113, %114, %115, %116, %117, %118, %119}, %120, %124, t, 1, 1, 0, 1;\n"
    "wgmma.mma_async.sync.aligned.m64n192k16.f32.bf16.bf16 {%0, %1, %2, %3, %4, %5, %6, %7, %8, %9, %10, %11, %12, %13, %14, %15, %16, %17, %18, %19, %20, %21, %22, %23, %24, %25, %26, %27, %28, %29, %30, %31, %32, %33, %34, %35, %36, %37, %38, %39, %40, %41, %42, %43, %44, %45, %46, %47, %48, %49, %50, %51, %52, %53, %54, %55, %56, %57, %58, %59, %60, %61, %62, %63, %64, %65, %66, %67, %68, %69, %70, %71, %72, %73, %74, %75, %76, %77, %78, %79, %80, %81, %82, %83, %84, %85, %86, %87, %88, %89, %90, %91, %92, %93, %94, %95}, %121, %123, t, 1, 1, 0, 1;\n"
    "wgmma.mma_async.sync.aligned.m64n48k16.f32.bf16.bf16 {%96, %97, %98, %99, %100, %101, %102, %103, %104, %105, %106, %107, %108, %109, %110, %111, %112, %113, %114, %115, %116, %117, %118, %119}, %121, %125, t, 1, 1, 0, 1;\n"
    "wgmma.commit_group.sync.aligned;\n"
    "}\n"
    : "+f"(d[0]), "+f"(d[1]), "+f"(d[2]), "+f"(d[3]), "+f"(d[4]), "+f"(d[5]), "+f"(d[6]), "+f"(d[7]), "+f"(d[8]), "+f"(d[9]), "+f"(d[10]), "+f"(d[11]), "+f"(d[12]), "+f"(d[13]), "+f"(d[14]), "+f"(d[15]), "+f"(d[16]), "+f"(d[17]), "+f"(d[18]), "+f"(d[19]), "+f"(d[20]), "+f"(d[21]), "+f"(d[22]), "+f"(d[23]), "+f"(d[24]), "+f"(d[25]), "+f"(d[26]), "+f"(d[27]), "+f"(d[28]), "+f"(d[29]), "+f"(d[30]), "+f"(d[31]), "+f"(d[32]), "+f"(d[33]), "+f"(d[34]), "+f"(d[35]), "+f"(d[36]), "+f"(d[37]), "+f"(d[38]), "+f"(d[39]), "+f"(d[40]), "+f"(d[41]), "+f"(d[42]), "+f"(d[43]), "+f"(d[44]), "+f"(d[45]), "+f"(d[46]), "+f"(d[47]), "+f"(d[48]), "+f"(d[49]), "+f"(d[50]), "+f"(d[51]), "+f"(d[52]), "+f"(d[53]), "+f"(d[54]), "+f"(d[55]), "+f"(d[56]), "+f"(d[57]), "+f"(d[58]), "+f"(d[59]), "+f"(d[60]), "+f"(d[61]), "+f"(d[62]), "+f"(d[63]), "+f"(d[64]), "+f"(d[65]), "+f"(d[66]), "+f"(d[67]), "+f"(d[68]), "+f"(d[69]), "+f"(d[70]), "+f"(d[71]), "+f"(d[72]), "+f"(d[73]), "+f"(d[74]), "+f"(d[75]), "+f"(d[76]), "+f"(d[77]), "+f"(d[78]), "+f"(d[79]), "+f"(d[80]), "+f"(d[81]), "+f"(d[82]), "+f"(d[83]), "+f"(d[84]), "+f"(d[85]), "+f"(d[86]), "+f"(d[87]), "+f"(d[88]), "+f"(d[89]), "+f"(d[90]), "+f"(d[91]), "+f"(d[92]), "+f"(d[93]), "+f"(d[94]), "+f"(d[95]), "+f"(d[96]), "+f"(d[97]), "+f"(d[98]), "+f"(d[99]), "+f"(d[100]), "+f"(d[101]), "+f"(d[102]), "+f"(d[103]), "+f"(d[104]), "+f"(d[105]), "+f"(d[106]), "+f"(d[107]), "+f"(d[108]), "+f"(d[109]), "+f"(d[110]), "+f"(d[111]), "+f"(d[112]), "+f"(d[113]), "+f"(d[114]), "+f"(d[115]), "+f"(d[116]), "+f"(d[117]), "+f"(d[118]), "+f"(d[119])
    : "l"(da), "l"(da + 2), "l"(db), "l"(db + 128), "l"(dn), "l"(dn + 32), "r"(wbar), "r"(wpar), "r"(abar), "r"(apar)
    : "memory");
}
__device__ __forceinline__ void iter_p_o(float* d, uint64_t da, uint64_t db, uint32_t wbar, uint32_t wpar, uint32_t abar, uint32_t apar) {
  asm volatile(
    "{\n"
    ".reg .pred s, t;\n"
    "mbarrier.test_wait.parity.shared::cta.b64 pw2, [%84], %85;\n"
    "mbarrier.test_wait.parity.shared::cta.b64 pa2, [%86], %87;\n"
    "setp.eq.b32 t, 0, 0;\n"
    "wgmma.fence.sync.aligned;\n"
    "wgmma.mma_async.sync.aligned.m64n160k16.f32.bf16.bf16 {%0, %1, %2, %3, %4, %5, %6, %7, %8, %9, %10, %11, %12, %13, %14, %15, %16, %17, %18, %19, %20, %21, %22, %23, %24, %25, %26, %27, %28, %29, %30, %31, %32, %33, %34, %35, %36, %37, %38, %39, %40, %41, %42, %43, %44, %45, %46, %47, %48, %49, %50, %51, %52, %53, %54, %55, %56, %57, %58, %59, %60, %61, %62, %63, %64, %65, %66, %67, %68, %69, %70, %71, %72, %73, %74, %75, %76, %77, %78, %79}, %80, %82, t, 1, 1, 0, 1;\n"
    "wgmma.mma_async.sync.aligned.m64n160k16.f32.bf16.bf16 {%0, %1, %2, %3, %4, %5, %6, %7, %8, %9, %10, %11, %12, %13, %14, %15, %16, %17, %18, %19, %20, %21, %22, %23, %24, %25, %26, %27, %28, %29, %30, %31, %32, %33, %34, %35, %36, %37, %38, %39, %40, %41, %42, %43, %44, %45, %46, %47, %48, %49, %50, %51, %52, %53, %54, %55, %56, %57, %58, %59, %60, %61, %62, %63, %64, %65, %66, %67, %68, %69, %70, %71, %72, %73, %74, %75, %76, %77, %78, %79}, %81, %83, t, 1, 1, 0, 1;\n"
    "wgmma.commit_group.sync.aligned;\n"
    "}\n"
    : "+f"(d[0]), "+f"(d[1]), "+f"(d[2]), "+f"(d[3]), "+f"(d[4]), "+f"(d[5]), "+f"(d[6]), "+f"(d[7]), "+f"(d[8]), "+f"(d[9]), "+f"(d[10]), "+f"(d[11]), "+f"(d[12]), "+f"(d[13]), "+f"(d[14]), "+f"(d[15]), "+f"(d[16]), "+f"(d[17]), "+f"(d[18]), "+f"(d[19]), "+f"(d[20]), "+f"(d[21]), "+f"(d[22]), "+f"(d[23]), "+f"(d[24]), "+f"(d[25]), "+f"(d[26]), "+f"(d[27]), "+f"(d[28]), "+f"(d[29]), "+f"(d[30]), "+f"(d[31]), "+f"(d[32]), "+f"(d[33]), "+f"(d[34]), "+f"(d[35]), "+f"(d[36]), "+f"(d[37]), "+f"(d[38]), "+f"(d[39]), "+f"(d[40]), "+f"(d[41]), "+f"(d[42]), "+f"(d[43]), "+f"(d[44]), "+f"(d[45]), "+f"(d[46]), "+f"(d[47]), "+f"(d[48]), "+f"(d[49]), "+f"(d[50]), "+f"(d[51]), "+f"(d[52]), "+f"(d[53]), "+f"(d[54]), "+f"(d[55]), "+f"(d[56]), "+f"(d[57]), "+f"(d[58]), "+f"(d[59]), "+f"(d[60]), "+f"(d[61]), "+f"(d[62]), "+f"(d[63]), "+f"(d[64]), "+f"(d[65]), "+f"(d[66]), "+f"(d[67]), "+f"(d[68]), "+f"(d[69]), "+f"(d[70]), "+f"(d[71]), "+f"(d[72]), "+f"(d[73]), "+f"(d[74]), "+f"(d[75]), "+f"(d[76]), "+f"(d[77]), "+f"(d[78]), "+f"(d[79])
    : "l"(da), "l"(da + 2), "l"(db), "l"(db + 128), "r"(wbar), "r"(wpar), "r"(abar), "r"(apar)
    : "memory");
}
__device__ __forceinline__ void iter_p_t(float* d, uint64_t da, uint64_t db) {
  asm volatile(
    "{\n"
    ".reg .pred t;\n"
    "setp.eq.b32 t, 0, 0;\n"
    "wgmma.fence.sync.aligned;\n"
    "wgmma.mma_async.sync.aligned.m64n160k16.f32.bf16.bf16 {%0, %1, %2, %3, %4, %5, %6, %7, %8, %9, %10, %11, %12, %13, %14, %15, %16, %17, %18, %19, %20, %21, %22, %23, %24, %25, %26, %27, %28, %29, %30, %31, %32, %33, %34, %35, %36, %37, %38, %39, %40, %41, %42, %43, %44, %45, %46, %47, %48, %49, %50, %51, %52, %53, %54, %55, %56, %57, %58, %59, %60, %61, %62, %63, %64, %65, %66, %67, %68, %69, %70, %71, %72, %73, %74, %75, %76, %77, %78, %79}, %80, %82, t, 1, 1, 0, 1;\n"
    "wgmma.mma_async.sync.aligned.m64n160k16.f32.bf16.bf16 {%0, %1, %2, %3, %4, %5, %6, %7, %8, %9, %10, %11, %12, %13, %14, %15, %16, %17, %18, %19, %20, %21, %22, %23, %24, %25, %26, %27, %28, %29, %30, %31, %32, %33, %34, %35, %36, %37, %38, %39, %40, %41, %42, %43, %44, %45, %46, %47, %48, %49, %50, %51, %52, %53, %54, %55, %56, %57, %58, %59, %60, %61, %62, %63, %64, %65, %66, %67, %68, %69, %70, %71, %72, %73, %74, %75, %76, %77, %78, %79}, %81, %83, t, 1, 1, 0, 1;\n"
    "wgmma.commit_group.sync.aligned;\n"
    "}\n"
    : "+f"(d[0]), "+f"(d[1]), "+f"(d[2]), "+f"(d[3]), "+f"(d[4]), "+f"(d[5]), "+f"(d[6]), "+f"(d[7]), "+f"(d[8]), "+f"(d[9]), "+f"(d[10]), "+f"(d[11]), "+f"(d[12]), "+f"(d[13]), "+f"(d[14]), "+f"(d[15]), "+f"(d[16]), "+f"(d[17]), "+f"(d[18]), "+f"(d[19]), "+f"(d[20]), "+f"(d[21]), "+f"(d[22]), "+f"(d[23]), "+f"(d[24]), "+f"(d[25]), "+f"(d[26]), "+f"(d[27]), "+f"(d[28]), "+f"(d[29]), "+f"(d[30]), "+f"(d[31]), "+f"(d[32]), "+f"(d[33]), "+f"(d[34]), "+f"(d[35]), "+f"(d[36]), "+f"(d[37]), "+f"(d[38]), "+f"(d[39]), "+f"(d[40]), "+f"(d[41]), "+f"(d[42]), "+f"(d[43]), "+f"(d[44]), "+f"(d[45]), "+f"(d[46]), "+f"(d[47]), "+f"(d[48]), "+f"(d[49]), "+f"(d[50]), "+f"(d[51]), "+f"(d[52]), "+f"(d[53]), "+f"(d[54]), "+f"(d[55]), "+f"(d[56]), "+f"(d[57]), "+f"(d[58]), "+f"(d[59]), "+f"(d[60]), "+f"(d[61]), "+f"(d[62]), "+f"(d[63]), "+f"(d[64]), "+f"(d[65]), "+f"(d[66]), "+f"(d[67]), "+f"(d[68]), "+f"(d[69]), "+f"(d[70]), "+f"(d[71]), "+f"(d[72]), "+f"(d[73]), "+f"(d[74]), "+f"(d[75]), "+f"(d[76]), "+f"(d[77]), "+f"(d[78]), "+f"(d[79])
    : "l"(da), "l"(da + 2), "l"(db), "l"(db + 128)
    : "memory");
}
__device__ __forceinline__ void iter_p_r(float* d, const uint32_t* a, uint64_t db, int sc) {
  asm volatile(
    "{\n"
    ".reg .pred s, t;\n"
    "setp.eq.b32 t, 0, 0;\n"
    "setp.ne.b32 s, %90, 0;\n"
    "wgmma.fence.sync.aligned;\n"
    "wgmma.mma_async.sync.aligned.m64n160k16.f32.bf16.bf16 {%0, %1, %2, %3, %4, %5, %6, %7, %8, %9, %10, %11, %12, %13, %14, %15, %16, %17, %18, %19, %20, %21, %22, %23, %24, %25, %26, %27, %28, %29, %30, %31, %32, %33, %34, %35, %36, %37, %38, %39, %40, %41, %42, %43, %44, %45, %46, %47, %48, %49, %50, %51, %52, %53, %54, %55, %56, %57, %58, %59, %60, %61, %62, %63, %64, %65, %66, %67, %68, %69, %70, %71, %72, %73, %74, %75, %76, %77, %78, %79}, {%80, %81, %82, %83}, %88, s, 1, 1, 1;\n"
    "wgmma.mma_async.sync.aligned.m64n160k16.f32.bf16.bf16 {%0, %1, %2, %3, %4, %5, %6, %7, %8, %9, %10, %11, %12, %13, %14, %15, %16, %17, %18, %19, %20, %21, %22, %23, %24, %25, %26, %27, %28, %29, %30, %31, %32, %33, %34, %35, %36, %37, %38, %39, %40, %41, %42, %43, %44, %45, %46, %47, %48, %49, %50, %51, %52, %53, %54, %55, %56, %57, %58, %59, %60, %61, %62, %63, %64, %65, %66, %67, %68, %69, %70, %71, %72, %73, %74, %75, %76, %77, %78, %79}, {%84, %85, %86, %87}, %89, t, 1, 1, 1;\n"
    "wgmma.commit_group.sync.aligned;\n"
    "}\n"
    : "+f"(d[0]), "+f"(d[1]), "+f"(d[2]), "+f"(d[3]), "+f"(d[4]), "+f"(d[5]), "+f"(d[6]), "+f"(d[7]), "+f"(d[8]), "+f"(d[9]), "+f"(d[10]), "+f"(d[11]), "+f"(d[12]), "+f"(d[13]), "+f"(d[14]), "+f"(d[15]), "+f"(d[16]), "+f"(d[17]), "+f"(d[18]), "+f"(d[19]), "+f"(d[20]), "+f"(d[21]), "+f"(d[22]), "+f"(d[23]), "+f"(d[24]), "+f"(d[25]), "+f"(d[26]), "+f"(d[27]), "+f"(d[28]), "+f"(d[29]), "+f"(d[30]), "+f"(d[31]), "+f"(d[32]), "+f"(d[33]), "+f"(d[34]), "+f"(d[35]), "+f"(d[36]), "+f"(d[37]), "+f"(d[38]), "+f"(d[39]), "+f"(d[40]), "+f"(d[41]), "+f"(d[42]), "+f"(d[43]), "+f"(d[44]), "+f"(d[45]), "+f"(d[46]), "+f"(d[47]), "+f"(d[48]), "+f"(d[49]), "+f"(d[50]), "+f"(d[51]), "+f"(d[52]), "+f"(d[53]), "+f"(d[54]), "+f"(d[55]), "+f"(d[56]), "+f"(d[57]), "+f"(d[58]), "+f"(d[59]), "+f"(d[60]), "+f"(d[61]), "+f"(d[62]), "+f"(d[63]), "+f"(d[64]), "+f"(d[65]), "+f"(d[66]), "+f"(d[67]), "+f"(d[68]), "+f"(d[69]), "+f"(d[70]), "+f"(d[71]), "+f"(d[72]), "+f"(d[73]), "+f"(d[74]), "+f"(d[75]), "+f"(d[76]), "+f"(d[77]), "+f"(d[78]), "+f"(d[79])
    : "r"(a[0]), "r"(a[1]), "r"(a[2]), "r"(a[3]), "r"(a[4]), "r"(a[5]), "r"(a[6]), "r"(a[7]), "l"(db), "l"(db + 128), "r"(sc)
    : "memory");
}
__device__ __forceinline__ void iter_qr_e(float* d, const uint32_t* a, uint64_t db, uint64_t dn, uint32_t wbar, uint32_t wpar, int sc) {
  asm volatile(
    "{\n"
    ".reg .pred s, t;\n"
    "mbarrier.test_wait.parity.shared::cta.b64 pw1, [%132], %133;\n"
    "setp.eq.b32 t, 0, 0;\n"
    "setp.ne.b32 s, %134, 0;\n"
    "wgmma.fence.sync.aligned;\n"
    "wgmma.mma_async.sync.aligned.m64n192k16.f32.bf16.bf16 {%0, %1, %2, %3, %4, %5, %6, %7, %8, %9, %10, %11, %12, %13, %14, %15, %16, %17, %18, %19, %20, %21, %22, %23, %24, %25, %26, %27, %28, %29, %30, %31, %32, %33, %34, %35, %36, %37, %38, %39, %40, %41, %42, %43, %44, %45, %46, %47, %48, %49, %50, %51, %52, %53, %54, %55, %56, %57, %58, %59, %60, %61, %62, %63, %64, %65, %66, %67, %68, %69, %70, %71, %72, %73, %74, %75, %76, %77, %78, %79, %80, %81, %82, %83, %84, %85, %86, %87, %88, %89, %90, %91, %92, %93, %94, %95}, {%120, %121, %122, %123}, %128, s, 1, 1, 1;\n"
    "wgmma.mma_async.sync.aligned.m64n48k16.f32.bf16.bf16 {%96, %97, %98, %99, %100, %101, %102, %103, %104, %105, %106, %107, %108, %109, %110, %111, %112, %113, %114, %115, %116, %117, %118, %119}, {%120, %121, %122, %123}, %130, s, 1, 1, 1;\n"
    "wgmma.mma_async.sync.aligned.m64n192k16.f32.bf16.bf16 {%0, %1, %2, %3, %4, %5, %6, %7, %8, %9, %10, %11, %12, %13, %14, %15, %16, %17, %18, %19, %20, %21, %22, %23, %24, %25, %26, %27, %28, %29, %30, %31, %32, %33, %34, %35, %36, %37, %38, %39, %40, %41, %42, %43, %44, %45, %46, %47, %48, %49, %50, %51, %52, %53, %54, %55, %56, %57, %58, %59, %60, %61, %62, %63, %64, %65, %66, %67, %68, %69, %70, %71, %72, %73, %74, %75, %76, %77, %78, %79, %80, %81, %82, %83, %84, %85, %86, %87, %88, %89, %90, %91, %92, %93, %94, %95}, {%124, %125, %126, %127}, %129, t, 1, 1, 1;\n"
    "wgmma.mma_async.sync.aligned.m64n48k16.f32.bf16.bf16 {%96, %97, %98, %99, %100, %101, %102, %103, %104, %105, %106, %107, %108, %109, %110, %111, %112, %113, %114, %115, %116, %117, %118, %119}, {%124, %125, %126, %127}, %131, t, 1, 1, 1;\n"
    "wgmma.commit_group.sync.aligned;\n"
    "}\n"
    : "+f"(d[0]), "+f"(d[1]), "+f"(d[2]), "+f"(d[3]), "+f"(d[4]), "+f"(d[5]), "+f"(d[6]), "+f"(d[7]), "+f"(d[8]), "+f"(d[9]), "+f"(d[10]), "+f"(d[11]), "+f"(d[12]), "+f"(d[13]), "+f"(d[14]), "+f"(d[15]), "+f"(d[16]), "+f"(d[17]), "+f"(d[18]), "+f"(d[19]), "+f"(d[20]), "+f"(d[21]), "+f"(d[22]), "+f"(d[23]), "+f"(d[24]), "+f"(d[25]), "+f"(d[26]), "+f"(d[27]), "+f"(d[28]), "+f"(d[29]), "+f"(d[30]), "+f"(d[31]), "+f"(d[32]), "+f"(d[33]), "+f"(d[34]), "+f"(d[35]), "+f"(d[36]), "+f"(d[37]), "+f"(d[38]), "+f"(d[39]), "+f"(d[40]), "+f"(d[41]), "+f"(d[42]), "+f"(d[43]), "+f"(d[44]), "+f"(d[45]), "+f"(d[46]), "+f"(d[47]), "+f"(d[48]), "+f"(d[49]), "+f"(d[50]), "+f"(d[51]), "+f"(d[52]), "+f"(d[53]), "+f"(d[54]), "+f"(d[55]), "+f"(d[56]), "+f"(d[57]), "+f"(d[58]), "+f"(d[59]), "+f"(d[60]), "+f"(d[61]), "+f"(d[62]), "+f"(d[63]), "+f"(d[64]), "+f"(d[65]), "+f"(d[66]), "+f"(d[67]), "+f"(d[68]), "+f"(d[69]), "+f"(d[70]), "+f"(d[71]), "+f"(d[72]), "+f"(d[73]), "+f"(d[74]), "+f"(d[75]), "+f"(d[76]), "+f"(d[77]), "+f"(d[78]), "+f"(d[79]), "+f"(d[80]), "+f"(d[81]), "+f"(d[82]), "+f"(d[83]), "+f"(d[84]), "+f"(d[85]), "+f"(d[86]), "+f"(d[87]), "+f"(d[88]), "+f"(d[89]), "+f"(d[90]), "+f"(d[91]), "+f"(d[92]), "+f"(d[93]), "+f"(d[94]), "+f"(d[95]), "+f"(d[96]), "+f"(d[97]), "+f"(d[98]), "+f"(d[99]), "+f"(d[100]), "+f"(d[101]), "+f"(d[102]), "+f"(d[103]), "+f"(d[104]), "+f"(d[105]), "+f"(d[106]), "+f"(d[107]), "+f"(d[108]), "+f"(d[109]), "+f"(d[110]), "+f"(d[111]), "+f"(d[112]), "+f"(d[113]), "+f"(d[114]), "+f"(d[115]), "+f"(d[116]), "+f"(d[117]), "+f"(d[118]), "+f"(d[119])
    : "r"(a[0]), "r"(a[1]), "r"(a[2]), "r"(a[3]), "r"(a[4]), "r"(a[5]), "r"(a[6]), "r"(a[7]), "l"(db), "l"(db + 128), "l"(dn), "l"(dn + 32), "r"(wbar), "r"(wpar), "r"(sc)
    : "memory");
}
__device__ __forceinline__ void iter_qr_o(float* d, const uint32_t* a, uint64_t db, uint64_t dn, uint32_t wbar, uint32_t wpar, uint32_t abar, uint32_t apar) {
  asm volatile(
    "{\n"
    ".reg .pred s, t;\n"
    "mbarrier.test_wait.parity.shared::cta.b64 pw1, [%132], %133;\n"
    "mbarrier.test_wait.parity.shared::cta.b64 pa1, [%134], %135;\n"
    "setp.eq.b32 t, 0, 0;\n"
    "wgmma.fence.sync.aligned;\n"
    "wgmma.mma_async.sync.aligned.m64n192k16.f32.bf16.bf16 {%0, %1, %2, %3, %4, %5, %6, %7, %8, %9, %10, %11, %12, %13, %14, %15, %16, %17, %18, %19, %20, %21, %22, %23, %24, %25, %26, %27, %28, %29, %30, %31, %32, %33, %34, %35, %36, %37, %38, %39, %40, %41, %42, %43, %44, %45, %46, %47, %48, %49, %50, %51, %52, %53, %54, %55, %56, %57, %58, %59, %60, %61, %62, %63, %64, %65, %66, %67, %68, %69, %70, %71, %72, %73, %74, %75, %76, %77, %78, %79, %80, %81, %82, %83, %84, %85, %86, %87, %88, %89, %90, %91, %92, %93, %94, %95}, {%120, %121, %122, %123}, %128, t, 1, 1, 1;\n"
    "wgmma.mma_async.sync.aligned.m64n48k16.f32.bf16.bf16 {%96, %97, %98, %99, %100, %101, %102, %103, %104, %105, %106, %107, %108, %109, %110, %111, %112, %113, %114, %115, %116, %117, %118, %119}, {%120, %121, %122, %123}, %130, t, 1, 1, 1;\n"
    "wgmma.mma_async.sync.aligned.m64n192k16.f32.bf16.bf16 {%0, %1, %2, %3, %4, %5, %6, %7, %8, %9, %10, %11, %12, %13, %14, %15, %16, %17, %18, %19, %20, %21, %22, %23, %24, %25, %26, %27, %28, %29, %30, %31, %32, %33, %34, %35, %36, %37, %38, %39, %40, %41, %42, %43, %44, %45, %46, %47, %48, %49, %50, %51, %52, %53, %54, %55, %56, %57, %58, %59, %60, %61, %62, %63, %64, %65, %66, %67, %68, %69, %70, %71, %72, %73, %74, %75, %76, %77, %78, %79, %80, %81, %82, %83, %84, %85, %86, %87, %88, %89, %90, %91, %92, %93, %94, %95}, {%124, %125, %126, %127}, %129, t, 1, 1, 1;\n"
    "wgmma.mma_async.sync.aligned.m64n48k16.f32.bf16.bf16 {%96, %97, %98, %99, %100, %101, %102, %103, %104, %105, %106, %107, %108, %109, %110, %111, %112, %113, %114, %115, %116, %117, %118, %119}, {%124, %125, %126, %127}, %131, t, 1, 1, 1;\n"
    "wgmma.commit_group.sync.aligned;\n"
    "}\n"
    : "+f"(d[0]), "+f"(d[1]), "+f"(d[2]), "+f"(d[3]), "+f"(d[4]), "+f"(d[5]), "+f"(d[6]), "+f"(d[7]), "+f"(d[8]), "+f"(d[9]), "+f"(d[10]), "+f"(d[11]), "+f"(d[12]), "+f"(d[13]), "+f"(d[14]), "+f"(d[15]), "+f"(d[16]), "+f"(d[17]), "+f"(d[18]), "+f"(d[19]), "+f"(d[20]), "+f"(d[21]), "+f"(d[22]), "+f"(d[23]), "+f"(d[24]), "+f"(d[25]), "+f"(d[26]), "+f"(d[27]), "+f"(d[28]), "+f"(d[29]), "+f"(d[30]), "+f"(d[31]), "+f"(d[32]), "+f"(d[33]), "+f"(d[34]), "+f"(d[35]), "+f"(d[36]), "+f"(d[37]), "+f"(d[38]), "+f"(d[39]), "+f"(d[40]), "+f"(d[41]), "+f"(d[42]), "+f"(d[43]), "+f"(d[44]), "+f"(d[45]), "+f"(d[46]), "+f"(d[47]), "+f"(d[48]), "+f"(d[49]), "+f"(d[50]), "+f"(d[51]), "+f"(d[52]), "+f"(d[53]), "+f"(d[54]), "+f"(d[55]), "+f"(d[56]), "+f"(d[57]), "+f"(d[58]), "+f"(d[59]), "+f"(d[60]), "+f"(d[61]), "+f"(d[62]), "+f"(d[63]), "+f"(d[64]), "+f"(d[65]), "+f"(d[66]), "+f"(d[67]), "+f"(d[68]), "+f"(d[69]), "+f"(d[70]), "+f"(d[71]), "+f"(d[72]), "+f"(d[73]), "+f"(d[74]), "+f"(d[75]), "+f"(d[76]), "+f"(d[77]), "+f"(d[78]), "+f"(d[79]), "+f"(d[80]), "+f"(d[81]), "+f"(d[82]), "+f"(d[83]), "+f"(d[84]), "+f"(d[85]), "+f"(d[86]), "+f"(d[87]), "+f"(d[88]), "+f"(d[89]), "+f"(d[90]), "+f"(d[91]), "+f"(d[92]), "+f"(d[93]), "+f"(d[94]), "+f"(d[95]), "+f"(d[96]), "+f"(d[97]), "+f"(d[98]), "+f"(d[99]), "+f"(d[100]), "+f"(d[101]), "+f"(d[102]), "+f"(d[103]), "+f"(d[104]), "+f"(d[105]), "+f"(d[106]), "+f"(d[107]), "+f"(d[108]), "+f"(d[109]), "+f"(d[110]), "+f"(d[111]), "+f"(d[112]), "+f"(d[113]), "+f"(d[114]), "+f"(d[115]), "+f"(d[116]), "+f"(d[117]), "+f"(d[118]), "+f"(d[119])
    : "r"(a[0]), "r"(a[1]), "r"(a[2]), "r"(a[3]), "r"(a[4]), "r"(a[5]), "r"(a[6]), "r"(a[7]), "l"(db), "l"(db + 128), "l"(dn), "l"(dn + 32), "r"(wbar), "r"(wpar), "r"(abar), "r"(apar)
    : "memory");
}
template <int PH>
__device__ __forceinline__ void iter_end_e(uint32_t& spin, uint32_t wbar, uint32_t wpar, uint32_t rel) {
  asm volatile(
    "{\n.reg .pred r;\n"
    "setp.ne.b32 r, %3, 0;\n"
    "wgmma.wait_group.sync.aligned 1;\n"
    "@r mbarrier.arrive.shared::cluster.b64 _, [%3];\n"
    "@pw%4 bra LAB_DONE;\n"
    "LAB_SLOW:\n"
    "mbarrier.try_wait.parity.shared::cta.b64 pw%4, [%1], %2;\n"
    "add.u32 %0, %0, 1;\n"
    "setp.lt.and.u32 r, %0, %5, !pw%4;\n"
    "@r bra LAB_SLOW;\n"
    "LAB_DONE:\n}"
    : "+r"(spin) : "r"(wbar), "r"(wpar), "r"(rel), "n"(PH), "n"(SPIN_MAX) : "memory");
}
template <int PH>
__device__ __forceinline__ void iter_end_o(uint32_t& spin, uint32_t wbar, uint32_t wpar, uint32_t abar, uint32_t apar, uint32_t rel) {
  asm volatile(
    "{\n.reg .pred r;\n"
    "setp.ne.b32 r, %5, 0;\n"
    "wgmma.wait_group.sync.aligned 1;\n"
    "@r mbarrier.arrive.shared::cluster.b64 _, [%5];\n"
    "and.pred r, pw%6, pa%6;\n"
    "@r bra LAB_DONE;\n"
    "LAB_SLOW:\n"
    "@!pw%6 mbarrier.try_wait.parity.shared::cta.b64 pw%6, [%1], %2;\n"
    "@!pa%6 mbarrier.try_wait.parity.shared::cta.b64 pa%6, [%3], %4;\n"
    "add.u32 %0, %0, 1;\n"
    "and.pred r, pw%6, pa%6;\n"
    "setp.lt.and.u32 r, %0, %7, !r;\n"
    "@r bra LAB_SLOW;\n"
    "LAB_DONE:\n}"
    : "+r"(spin) : "r"(wbar), "r"(wpar), "r"(abar), "r"(apar), "r"(rel), "n"(PH), "n"(SPIN_MAX) : "memory");
}

template <class F>
__device__ __forceinline__ void attention(uint32_t* q, uint32_t kplane, int lane, bool first, float glo, float ghi, F drained) {
  constexpr float C = 0.22360679774997896f * 1.4426950408889634f;
  const int rho = lane >> 2, qd = lane & 3, m = lane >> 3, row = lane & 7;
  const bool gt0 = 2 * qd > rho, gt1 = 2 * qd + 1 > rho;
  const uint32_t M = (gt0 ? 0xffffu : 0u) | (gt1 ? 0xffff0000u : 0u);
  const uint32_t mA = qd < 2 ? 0xffffffffu : 0u;
  const uint32_t ra = kplane + 160 * row + 16 * (row >> 2);
  const uint32_t aA = ra + 16 * m, aB = ra + 1312 * (m < 2 ? m : 2) + 64;
  float s[4][3][4];
  {
    uint32_t k[2][3][5];
#pragma unroll
    for (int pr = 0; pr < 2; pr++) {
      uint32_t kb[4];
#pragma unroll
      for (int t = 0; t < 3; t++) ldsm4(k[pr][t], aA + 80 * pr + 1312 * t);
      ldsm4(kb, aB + 80 * pr);
#pragma unroll
      for (int t = 0; t < 3; t++) k[pr][t][4] = kb[t];
    }
    drained();
#pragma unroll
    for (int pr = 0; pr < 2; pr++)
#pragma unroll
      for (int t = 0; t < 3; t++) {
        const uint32_t* qq = q + 10 * pr;
        mma16z(s[2 * pr][t], qq[0], qq[1], qq[2], qq[3], k[pr][t][0], k[pr][t][1]);
        mma16z(s[2 * pr + 1][t], qq[6], qq[7], qq[8], qq[9], k[pr][t][3], k[pr][t][4]);
      }
#pragma unroll
    for (int pr = 0; pr < 2; pr++)
#pragma unroll
      for (int t = 0; t < 3; t++) {
        const uint32_t* qq = q + 10 * pr;
        mma8(s[2 * pr][t], qq[4] & mA, qq[5] & mA, k[pr][t][2]);
        mma8(s[2 * pr + 1][t], qq[4] & ~mA, qq[5] & ~mA, k[pr][t][2]);
      }
  }
  float e[4][4], ml[4], mh[4];
#pragma unroll
  for (int h = 0; h < 4; h++) {
    e[h][0] = gt0 ? s[h][0][0] : s[h][1][0]; e[h][1] = gt1 ? s[h][0][1] : s[h][1][1];
    e[h][2] = gt0 ? s[h][1][2] : s[h][2][2]; e[h][3] = gt1 ? s[h][1][3] : s[h][2][3];
    if (first) {
      if (gt0) e[h][0] = -1e9f;
      if (gt1) e[h][1] = -1e9f;
    }
    ml[h] = fmaxf(e[h][0], e[h][1]); mh[h] = fmaxf(e[h][2], e[h][3]);
  }
  uint32_t v[2][3][5];
#pragma unroll
  for (int pr = 0; pr < 2; pr++) {
    uint32_t vb[4];
#pragma unroll
    for (int t = 0; t < 3; t++) ldsm4t(v[pr][t], aA + 80 * pr + 2 * PLANE + 1312 * t);
    ldsm4t(vb, aB + 80 * pr + 2 * PLANE);
#pragma unroll
    for (int t = 0; t < 3; t++) v[pr][t][4] = vb[t];
  }
#pragma unroll
  for (int x = 1; x <= 2; x++)
#pragma unroll
    for (int h = 0; h < 4; h++) { ml[h] = fmaxf(ml[h], __shfl_xor_sync(0xffffffffu, ml[h], x)); mh[h] = fmaxf(mh[h], __shfl_xor_sync(0xffffffffu, mh[h], x)); }
#pragma unroll
  for (int h = 0; h < 4; h++) {
    const float nl = -ml[h] * C, nh = -mh[h] * C;
    e[h][0] = ex2(fmaf(e[h][0], C, nl)); e[h][1] = ex2(fmaf(e[h][1], C, nl)); e[h][2] = ex2(fmaf(e[h][2], C, nh)); e[h][3] = ex2(fmaf(e[h][3], C, nh));
    ml[h] = e[h][0] + e[h][1]; mh[h] = e[h][2] + e[h][3];
  }
#pragma unroll
  for (int x = 1; x <= 2; x++)
#pragma unroll
    for (int h = 0; h < 4; h++) { ml[h] += __shfl_xor_sync(0xffffffffu, ml[h], x); mh[h] += __shfl_xor_sync(0xffffffffu, mh[h], x); }
  uint32_t a0[4], a2[4], a3[4], a5[4];
#pragma unroll
  for (int h = 0; h < 4; h++) {
    const float fl = glo * rcp(ml[h]), fh = ghi * rcp(mh[h]);
    const uint32_t plo = pack_bf16(e[h][0] * fl, e[h][1] * fl), phi = pack_bf16(e[h][2] * fh, e[h][3] * fh);
    a0[h] = plo & M; a2[h] = plo & ~M; a3[h] = phi & M; a5[h] = phi & ~M;
  }
  float o[4][3][4];
#pragma unroll
  for (int h = 0; h < 4; h++)
#pragma unroll
    for (int c = 0; c < 3; c++) mma16z(o[h][c], a0[h], 0u, a2[h], a3[h], v[h >> 1][0][2 * (h & 1) + c], v[h >> 1][1][2 * (h & 1) + c]);
#pragma unroll
  for (int h = 0; h < 4; h++)
#pragma unroll
    for (int c = 0; c < 3; c++) mma8(o[h][c], 0u, a5[h], v[h >> 1][2][2 * (h & 1) + c]);
#pragma unroll
  for (int pr = 0; pr < 2; pr++) {
    const float (*o0)[4] = o[2 * pr], (*o1)[4] = o[2 * pr + 1];
    uint32_t* oo = q + 10 * pr;
    oo[0] = pack_bf16(o0[0][0], o0[0][1]); oo[1] = pack_bf16(o0[0][2], o0[0][3]);
    oo[2] = pack_bf16(o0[1][0], o0[1][1]); oo[3] = pack_bf16(o0[1][2], o0[1][3]);
    oo[4] = qd < 2 ? pack_bf16(o0[2][0], o0[2][1]) : pack_bf16(o1[0][0], o1[0][1]);
    oo[5] = qd < 2 ? pack_bf16(o0[2][2], o0[2][3]) : pack_bf16(o1[0][2], o1[0][3]);
    oo[6] = pack_bf16(o1[1][0], o1[1][1]); oo[7] = pack_bf16(o1[1][2], o1[1][3]);
    oo[8] = pack_bf16(o1[2][0], o1[2][1]); oo[9] = pack_bf16(o1[2][2], o1[2][3]);
  }
}

__device__ __forceinline__ uint32_t read_tag() { return (*reinterpret_cast<volatile uint32_t*>(&g_done) >> 7) + 1; }
__device__ __forceinline__ uint32_t clock32() { uint32_t c; asm volatile("mov.u32 %0, %%clock;" : "=r"(c)); return c; }

__device__ __forceinline__ void watch_flags(const uint32_t* fl, uint32_t base, int& lv0, int until, uint32_t sig, uint32_t& spin) {
#pragma unroll 1
  while (lv0 <= until) {
    const uint4 v = ld_acquire4(fl);
    const int lv = min(min((int)(v.x - base), (int)(v.y - base)), min((int)(v.z - base), (int)(v.w - base)));
    if (++spin >= SPIN_MAX) break;
    if (lv >= lv0) {
      fence_async_glob();
#pragma unroll 1
      for (; lv0 <= lv; lv0++) if (sig) mbar_arrive(sig + 8 * (lv0 - 1));
    }
  }
}

struct Ring {
  int pa;
  int ua;
  int sw;
  uint32_t pw;
  uint32_t spin;
};

#define TRB(n) do {} while (0)

template <int PH, class F, class FE, class FO, class FT>
__device__ __forceinline__ void mma_loop(float* acc, Ring& rg, uint32_t bar, uint32_t rel, uint32_t dlo_a, uint32_t dlo_b, uint32_t lda, uint32_t ldx,
                                         int lane, bool lead, int trbase, F mid, FE hook_e, FO hook_o, FT tail) {
  constexpr int NP = PH == 2 ? (N_P3 - NW) / 2 : 10;
  constexpr int HOLD = PH == 0 ? HOLD_H : (PH == 1 ? HOLD_Q : HOLD_P);
  constexpr uint64_t DHI = (uint64_t)((1024u >> 4) | (1u << 30)) << 32;
  constexpr uint64_t DNH = (uint64_t)((256u >> 4) | (3u << 30)) << 32;
  asm volatile(".reg .pred pw%0, pa%0;" ::"n"(PH));
  uint32_t da = dlo_a + rg.pa * (PAGE >> 4), dbe = dlo_b + rg.sw * (PAGE >> 4), dbo;
  uint32_t rele = 0, relo;
  int swe = rg.sw;
  if (++rg.sw == NW) { rg.sw = 0; rg.pw ^= 1; }
  uint32_t wbo = bar + 8 * (B_WF + rg.sw), wpo = rg.pw, wbe, wpe, ab, ap;
  const int holdm = PH == 2 || HOLD == 0 || lead ? -1 : (20 - HOLD) / 2 - 1, arrm = PH != 2 && HOLD > 0 && lead ? NP - 1 : -1;
  int ev = PH == 2 ? ATT_POS / 2 - 1 : holdm;
  const bool isw = lane < 2, isa = lane == 2;
#pragma unroll 1
  for (int m = 0; m < NP; m++) {
    TRB(2 * m);
    if (PH == 0) iter_h_e(acc, DHI | da, DHI | dbe, wbo, wpo, 1);
    if (PH == 1) {
      uint32_t af[8];
      ldsm4(af, lda + rg.pa * PAGE + ldx); ldsm4(af + 4, lda + rg.pa * PAGE + (ldx ^ 32));
      iter_qr_e(acc, af, DHI | dbe, DNH | ((dbe + 768u) & 0xffffu) | ((1024u >> 4) << 16), wbo, wpo, m);
    }
    if (PH == 2) iter_p_e(acc, DHI | da, DHI | dbe, wbo, wpo, m);
    dbo = dlo_b + rg.sw * (PAGE >> 4);
    relo = isw ? rel + 8 * swe : 0u;
    const int swo = rg.sw;
    if (++rg.sw == NW) { rg.sw = 0; rg.pw ^= 1; }
    wbe = bar + 8 * (B_WF + rg.sw); wpe = rg.pw;
    {
      const bool newa = PH == 0 ? m < NP - 1 : (PH == 1 ? m >= 3 : true);
      rg.ua += newa;
      ab = bar + 8 * (newa ? B_AF + (rg.ua & 3) : B_DUMMY); ap = newa ? (rg.ua >> 2) & 1 : 1u;
    }
    hook_e(m);
    iter_end_e<PH>(rg.spin, wbo, wpo, rele);
    TRB(2 * m + 1);
    if (PH == 0) iter_h_o(acc, DHI | (da + 4), DHI | dbo, wbe, wpe, ab, ap);
    if (PH == 1) {
      uint32_t ag[8];
      ldsm4(ag, lda + rg.pa * PAGE + (ldx ^ 64)); ldsm4(ag + 4, lda + rg.pa * PAGE + (ldx ^ 96));
      iter_qr_o(acc, ag, DHI | dbo, DNH | ((dbo + 768u) & 0xffffu) | ((1024u >> 4) << 16), wbe, wpe, ab, ap);
    }
    if (PH == 2) iter_p_o(acc, DHI | (da + 4), DHI | dbo, wbe, wpe, ab, ap);
    if (m == arrm) asm volatile("bar.arrive %0, 256;" ::"n"(3 + PH) : "memory");
    dbe = dlo_b + rg.sw * (PAGE >> 4);
    {
      const bool rela = PH != 0 || m < 6;
      const uint32_t idx = isw ? swo : rg.pa;
      rele = (isw | (isa & rela)) ? rel + 8 * idx : 0u;
    }
    rg.pa = (rg.pa + 1) & 3;
    da = dlo_a + rg.pa * (PAGE >> 4);
    swe = rg.sw;
    if (++rg.sw == NW) { rg.sw = 0; rg.pw ^= 1; }
    wbo = bar + 8 * (B_WF + rg.sw); wpo = rg.pw;
    hook_o(m);
    iter_end_o<PH>(rg.spin, wbe, wpe, ab, ap, relo);
    if (__builtin_expect(m == ev, 0)) {
      auto drain = [&]() {
        wg_wait<0>();
        if (rele) mbar_arrive_remote(rele);
        rele = 0;
      };
      if (PH == 2 && m == ATT_POS / 2 - 1) { mid(drain); ev = holdm; }
      else { drain(); asm volatile("bar.sync %0, 256;" ::"n"(3 + PH) : "memory"); }
    }
  }
  rg.sw = swe; rg.pw = wpe;
  if (PH == 2) {
    static_assert((N_H + N_QKV + N_P3 - NW) % NW == 0 && (N_H + N_QKV + N_P3 - NW) / NW % 2 == 0 && N_P3 - NW == 30, "tail");
    if (HOLD > 0 && !lead) {
      wg_wait<0>();
      if (rele) mbar_arrive_remote(rele);
      asm volatile("bar.sync 5, 256;" ::: "memory");
    }
#pragma unroll
    for (int k = 0; k < NW; k++) {
      constexpr int U0 = 31;
      if (k > 0) {
        mbar_wait(bar + 8 * (B_WF + k), 0, rg.spin);
        if ((k & 1) == 0) mbar_wait(bar + 8 * (B_AF + ((U0 + k / 2) & 3)), ((U0 + k / 2) >> 2) & 1, rg.spin);
      }
      if (HOLD > 0 && k == TAILREL && lead) asm volatile("bar.arrive 5, 256;" ::: "memory");
      TRB(N_P3 - NW + k);
      iter_p_t(acc, DHI | (dlo_a + ((U0 + k / 2) & 3) * (PAGE >> 4) + (k & 1) * 4), DHI | (dlo_b + k * (PAGE >> 4)));
      if (k == 0 && (HOLD == 0 || lead)) {
        wg_wait<1>();
        if (rele) mbar_arrive_remote(rele);
      }
    }
    tail();
  }
  wg_wait<0>();
  fence_regs<PH == 0 ? 108 : (PH == 1 ? 120 : 80)>(acc);
  if (PH != 2 && rele) mbar_arrive_remote(rele);
}

__global__ void __cluster_dims__(2, 1, 1) __launch_bounds__(NTHREADS, 1)
fused_kernel(const __nv_bfloat16* __restrict__ px, const __nv_bfloat16* __restrict__ pw1, const __nv_bfloat16* __restrict__ pb1, const __nv_bfloat16* __restrict__ pgate,
             __nv_bfloat16* __restrict__ pout, const __nv_bfloat16* __restrict__ pb2, const __grid_constant__ Params p) {
  extern __shared__ __align__(1024) uint8_t smem_raw[];
  const uint32_t sb = smem_u32(smem_raw);
  const uint32_t bar = sb + BAR_OFF;
  const int tid = threadIdx.x;
  const int warp = __shfl_sync(0xffffffffu, tid >> 5, 0);
  const int lane_ = tid & 31;
#define TC(v) do {} while (0)
  const int r = blockIdx.x & 1;
  const int c_ = blockIdx.x >> 1;
  const int L = c_ < 4 ? 4 + c_ : (c_ < 36 ? ((c_ - 4) & 7) * 8 + ((c_ - 4) >> 3) : (1 + (c_ - 36) % 7) * 8 + 4 + (c_ - 36) / 7);
  const int G = L >> 3, pp = L & 7;
  const int i = 4 * (G >> 1) + 2 * (pp >> 2) + r;
  const int j = 4 * (G & 1) + (pp & 3);
  const int t = pp & 3, kh = G & 1;
  const uint32_t cs = i * 8 + j;
  uint32_t spin = 0;

  constexpr int N_EARLY = 2;
  const uint8_t* pf = nullptr;
  uint32_t pfs = 0;
  if (warp == 3) {
    const int lane = lane_;
    pf = lane < 16 ? reinterpret_cast<const uint8_t*>(px) + (16 * cs + lane) * (DM * 2) : reinterpret_cast<const uint8_t*>(pw1) + (cs * 1728 + (lane - 16) * 128);
    pfs = lane < 16 ? 128u : 64u * FF * 2u;
    if (lane < 30) { prefetch_l2(pf); prefetch_l2(pf + pfs); }
  }
  auto early = [&]() {
    mbar_expect_tx(bar + 8 * B_AF, PAGE);
    tma_4d(sb, &p.a[0], 0, 0, 0, 4 * i, bar + 8 * B_AF);
#pragma unroll
    for (int n = 0; n < N_EARLY; n++) {
      const uint32_t fb = bar + 8 * (B_WF + n), dst = sb + WB + n * PAGE;
      mbar_expect_tx(fb, BYTES_W1);
      tma_4d(dst, &p.w[0], 0, n * 32, 0, j, fb);
      tma_4d(dst + 12288, &p.w[1], 0, n * 32, 0, j, fb);
    }
  };
  if (warp < 2) {
    if (elect_one()) {
      if (warp == 0) {
        mbar_init(bar + 8 * B_AF, 1);
#pragma unroll
        for (int b = 0; b < N_EARLY; b++) mbar_init(bar + 8 * (B_WF + b), 1);
        fence_async_smem();
        TC(tc1);
        early();
        TC(tc3);
      } else {
#pragma unroll
        for (int b = 1; b < B_NBAR; b++) {
          if (b >= B_WF && b < B_WF + N_EARLY) continue;
          mbar_init(bar + 8 * b, b >= B_WE && b < B_WE + NW ? 16 : ((b >= B_AE && b < B_AE + NA) || b >= B_HDONE || b == B_ODONE ? 8 : (b == B_GREADY || b == B_KV || b == B_HALO ? 2 : 1)));
        }
      }
      asm volatile("fence.mbarrier_init.release.cluster;" ::: "memory");
      fence_async_smem();
    }
    __syncwarp();
  }
  TC(tc2);
  cluster_arrive();
  TC(tc5);
  if (warp < 4) {
    const int lane = lane_;
    asm volatile("setmaxnreg.dec.sync.aligned.u32 %0;" ::"n"(REG_P));
    asm volatile("{\n.reg .pred p;\nsetp.ne.u32 p, %0, 0;\n@p trap;\n}" ::"r"(sb & 1023));
    if (warp != 1) cluster_wait();
    if (warp < 1) {
      if (elect_one()) {
        int sl = N_EARLY; uint32_t ph = 1;
        uint32_t dst0 = sb + WB + (r == 0 ? 0u : 12288u), bytes = BYTES_W1;
        const CUtensorMap* tm = &p.w[r];
        int c3 = j, kn = 32 * N_EARLY, cnt = N_H - N_EARLY;
#pragma unroll 1
        for (int s = 0; s < 6; s++) {
          if (s == 1) { bytes = 15360; kn = 384; cnt = N_QKV; }
          if (s == 2) { c3 = t; dst0 -= 4096 * r; bytes = BYTES_W2; cnt = 24; }
          if (s == 3) { kn = 1536 + 96 * kh; cnt = 2; }
          if (s == 4) { kn = 320 * kh; cnt = 10; }
          if (s == 5) { kn = 1600 + 96 * kh; cnt = 1; tm -= 4; }
          if (s != 0 && s != 3) tm += 2;
#pragma unroll 1
          for (int m = 0; m < cnt; m++) {
            int k = kn;
            kn += 32;
            if (s == 1 && kn == DM) kn = 0;
            if (s == 2) k = 768 * kh + 192 * ((t + (m >> 1)) & 3) + 64 * (m >> 3) + 32 * (m & 1);
            mbar_wait(bar + 8 * (B_WE + sl), ph, spin);
            mbar_expect_tx(bar + 8 * (B_WF + sl), bytes);
            tma_4d_mc(dst0 + sl * PAGE, tm, 0, k, 0, c3, bar + 8 * (B_WF + sl));
            if (++sl == NW) { sl = 0; ph ^= 1; }
          }
        }
      }
    } else if (warp < 2) {
      if (elect_one()) {
#pragma unroll 1
        for (int u = 1; u < 35; u++) {
          if (u == 4) {
#pragma unroll 1
            for (int m = 2; m < 15; m++) prefetch_tmap(reinterpret_cast<const CUtensorMap*>(&p) + m);
          }
          if (u == 6) {
            l2_prefetch(reinterpret_cast<const uint8_t*>(p.pwqkv) + cs * 19200u, 19200);
            l2_prefetch(reinterpret_cast<const uint8_t*>(p.pw2) + cs * 17280u, 17280);
            l2_prefetch(reinterpret_cast<const uint8_t*>(p.pwo) + cs * 6400u, 6400);
          }
          int k = 64 * (u < 10 ? u : u - 10), need = -1;
          const CUtensorMap* tm = &p.a[0];
          if (u >= 16) {
            const int m = u - 16;
            tm = &p.a[1];
            k = 768 * kh + 192 * ((t + m) & 3) + 64 * (m >> 2);
            if ((m & 3) == 0) need = m >> 2;
            if (u == 28) k = 1536 + 96 * kh;
            if (u >= 29) { tm = &p.a[2]; k = 320 * kh + 64 * (u - 29); need = u == 29 ? 4 : -1; }
            if (u == 34) { tm = &p.a[1]; k = 1600 + 96 * kh; }
          }
          if (need >= 0) {
            mbar_wait(bar + 8 * (B_LV + need), 0, spin);
            TR(u == 29 ? 39 : 40 + need);
          }
          const int sl = u & 3;
          mbar_wait(bar + 8 * (B_AE + sl), ((u >> 2) & 1) ^ 1, spin);
          mbar_expect_tx(bar + 8 * (B_AF + sl), PAGE);
          tma_4d(sb + sl * PAGE, tm, k, 0, 0, 4 * i, bar + 8 * (B_AF + sl));
          TRW(150 + u);
        }
      }
    } else {
      const int w2 = warp - 2;
      const uint32_t tag = read_tag();
      {
        mbar_wait(bar + 8 * B_AF, 0, spin);
#define PFPACE 0
        if (w2 == 1 && lane < 30) {
#pragma unroll 1
          for (int m = 2; m < 10; m++) {
            if (PFPACE > 0) { const uint32_t t1 = clock32(); while (m > 2 && clock32() - t1 < PFPACE) {} }
            prefetch_l2(pf + (size_t)m * pfs);
          }
        }
        if (w2 == 0) {
          sts128(sb + R0 + ZERO_OFF + 16 * lane, make_uint4(0u, 0u, 0u, 0u)); sts128(sb + R0 + ZERO_OFF + 512 + 16 * lane, make_uint4(0u, 0u, 0u, 0u));
          sts128(sb + R0 + ZERO_OFF + 1024 + 16 * lane, make_uint4(0u, 0u, 0u, 0u)); sts128(sb + R0 + ZERO_OFF + 1536 + 16 * lane, make_uint4(0u, 0u, 0u, 0u));
          fence_async_smem();
          __syncwarp();
        }
        if (w2 == 0 && elect_one()) {
          mbar_expect_tx(bar + 8 * B_XG, 17 * DM * 2);
          bulk_load(sb + R0, reinterpret_cast<const uint8_t*>(px) + cs * (16u * DM * 2u), 16 * DM * 2, bar + 8 * B_XG);
          bulk_load(sb + R0 + 16 * DM * 2, pgate, DM * 2, bar + 8 * B_XG);
        }
        if (w2 == 1 && lane < 20) {
          const __nv_bfloat16* bp = pb2 + (lane < 16 ? 128 * t : 512 + 32 * t - 128);
          sts128(sb + BIAS_OFF + 16 * lane, __ldg(reinterpret_cast<const uint4*>(bp) + lane));
        }
        mbar_wait(bar + 8 * B_XG, 0, spin);
        float s0 = 0.f, s1 = 0.f;
        const uint32_t xa = sb + R0 + (8 * w2 + (lane >> 2)) * (DM * 2) + 16 * (lane & 3), wa = sb + R0 + 16 * DM * 2 + 16 * (lane & 3);
#pragma unroll 2
        for (int c = 0; c < 20; c++) {
          const uint4 x = lds128(xa + 64 * c), w = lds128(wa + 64 * c);
          const uint32_t a = mul_bf16x2(x.x, w.x), b = mul_bf16x2(x.y, w.y), d = mul_bf16x2(x.z, w.z), e = mul_bf16x2(x.w, w.w);
          s0 += (bf_lo(a) + bf_hi(a)) + (bf_lo(b) + bf_hi(b));
          s1 += (bf_lo(d) + bf_hi(d)) + (bf_lo(e) + bf_hi(e));
        }
        s0 += s1;
        s0 += __shfl_xor_sync(0xffffffffu, s0, 1);
        s0 += __shfl_xor_sync(0xffffffffu, s0, 2);
        if ((lane & 3) == 0) {
          const float z = __bfloat162float(__float2bfloat16(s0));
          const float g = rcp(1.f + ex2(z * -1.4426950408889634f));
          st_ll(&g_gateLL[16 * cs + 8 * w2 + (lane >> 2)], (uint32_t)__bfloat16_as_ushort(__float2bfloat16(g)), tag);
        }
        if (lane == 0 && warp == 2) TR(11);
        if (w2 == 0 && elect_one()) {
#pragma unroll 1
          for (int c = 0; c < 4; c++) {
            const int c3 = 4 * i + 2 * kh + (c >> 1);
            tma_store_4d(&p.outw, sb + R0 + ZERO_OFF, 128 * t, 0, c & 1, c3);
            tma_store_4d(&p.outw, sb + R0 + ZERO_OFF, 128 * t + 64, 0, c & 1, c3);
            tma_store_4d(&p.outn, sb + R0 + ZERO_OFF, 512 + 32 * t, 0, c & 1, c3);
          }
          asm volatile("cp.async.bulk.commit_group;" ::: "memory");
        }
        {
          const int row = 64 * w2 + 2 * lane;
          ulonglong2 v;
          do { v = ld_ll2(reinterpret_cast<const ulonglong2*>(g_gateLL + (128 * i + row))); }
          while (((uint32_t)(v.x >> 32) != tag || (uint32_t)(v.y >> 32) != tag) && ++spin < SPIN_MAX);
          sts32(sb + G_OFF + 2 * row, (uint32_t)v.x | ((uint32_t)v.y << 16));
        }
        if (lane == 0) sts32(sb + TAG_OFF, tag);
        __syncwarp();
        if (w2 == 0 && elect_one()) asm volatile("cp.async.bulk.wait_group.read 0;" ::: "memory");
        __syncwarp();
        if (lane == 0) { mbar_arrive(bar + 8 * B_GREADY); if (warp == 2) TR(2); }
        if (lane == 0 && warp == 2) TR(13);
      }
      const uint32_t* fl = g_flag + i * 32;
      int lv = 1;
      if (w2 == 0) {
        if (elect_one()) {
          uint32_t* flag = g_flag + i * 32 + j;
          mbar_wait(bar + 8 * B_HDONE, 0, spin);
          const uint32_t t0 = clock32();
#pragma unroll 1
          for (int q = 0; q < 12; q++) {
            const int pc = q >> 2;
            if ((q & 3) == 0) { mbar_wait(bar + 8 * (B_HDONE + pc), 0, spin); TR(33 + pc); fence_async_smem(); }
            while (clock32() - t0 < H_PACE * (uint32_t)q) {}
            tma_store_4d(&p.hst, sb + R0 + q * 4096, 192 * j + 64 * pc, 0, 0, 4 * i + (q & 3));
            asm volatile("cp.async.bulk.commit_group;" ::: "memory");
            if ((q & 3) == 0 && q > 0 && ((RELMASK >> (pc - 1)) & 1)) {
              asm volatile("cp.async.bulk.wait_group 1;" ::: "memory");
              TR(35 + pc);
              st_flag(flag, 4 * (tag - 1) + pc);
              TR(44 + pc);
            }
          }
          asm volatile("cp.async.bulk.wait_group.read 0;" ::: "memory");
          mbar_arrive(bar + 8 * B_HFREE);
        }
      } else if (lane == 0) {
        mbar_wait(bar + 8 * B_HDONE, 0, spin);
        watch_flags(fl + 4 * (1 - kh), 4 * (tag - 1), lv, 1, 0, spin);
        lv = 1;
        watch_flags(fl + 4 * kh, 4 * (tag - 1), lv, WATCH1, bar + 8 * B_LV, spin);
      }
      __syncwarp();
      mbar_wait(bar + 8 * B_KV, 0, spin);
      mbar_wait(bar + 8 * B_HFREE, 0, spin);
      if (w2 == 1) TR(51);
      {
        const uint32_t* hint = g_flag + (i > 0 ? i - 1 : 0) * 32 + 16 + 2 * j + w2;
        while (ld_relaxed(hint) != tag && ++spin < SPIN_MAX) {}
        const ulonglong2* src = g_halo + (((i > 0 ? cs - 8 : cs) * 2 + w2) * 320 + lane);
        ulonglong2 v[10];
        uint32_t bad;
        do {
          bad = 0;
#pragma unroll
          for (int c = 0; c < 10; c++) { v[c] = ld_ll2(src + 32 * c); bad |= ((uint32_t)(v[c].x >> 32) ^ tag) | ((uint32_t)(v[c].y >> 32) ^ tag); }
        } while (bad && ++spin < SPIN_MAX);
        const uint32_t dst = sb + R0 + w2 * PLANE + roff(lane >> 2) + 4 * (lane & 3);
#pragma unroll
        for (int c = 0; c < 10; c++) {
          sts32(dst + (c / 5) * 2 * PLANE + (c % 5) * 32, (uint32_t)v[c].x);
          sts32(dst + (c / 5) * 2 * PLANE + (c % 5) * 32 + 16, (uint32_t)v[c].y);
        }
      }
      __syncwarp();
      if (lane == 0) mbar_arrive(bar + 8 * B_HALO);
      if (w2 == 0) {
        if (elect_one()) {
          mbar_wait(bar + 8 * (B_HDONE + 3), 0, spin);
          asm volatile("cp.async.bulk.wait_group 0;" ::: "memory");
          TR(47);
          st_flag(g_flag + i * 32 + j, 4 * tag);
          TR(48);
        }
        __syncwarp();
        if (elect_one()) {
          mbar_wait(bar + 8 * B_ODONE, 0, spin);
          fence_async_smem();
          tma_store_4d(&p.ost, sb + R0, 80 * j, 0, 0, 4 * i);
          asm volatile("cp.async.bulk.commit_group;" ::: "memory");
          asm volatile("cp.async.bulk.wait_group 0;" ::: "memory");
          TR(49);
          st_flag(g_flag + i * 32 + j + 8, 4 * tag);
          TR(50);
        }
      } else if (lane == 0) {
        TR(54);
        watch_flags(fl + 4 * kh, 4 * (tag - 1), lv, 4, bar + 8 * B_LV, spin);
        lv = 4;
        watch_flags(fl + 8 + 4 * kh, 4 * (tag - 1), lv, 4, bar + 8 * (B_LV + 1), spin);
      }
    }
  } else {
    uint32_t bw[27];
    {
      const uint32_t* b1w = reinterpret_cast<const uint32_t*>(pb1);
#pragma unroll
      for (int g8 = 0; g8 < 27; g8++) bw[g8] = __ldg(b1w + (uint32_t)((g8 < 24 ? 96 * j + 4 * g8 : 768 + 12 * j + 4 * (g8 - 24)) + (lane_ & 3)));
    }
    asm volatile("setmaxnreg.inc.sync.aligned.u32 %0;" ::"n"(REG_C));
    const int lane = __shfl_sync(0xffffffffu, lane_, lane_);
    const int w8 = warp - 4, cw = w8 >> 2;
    const uint32_t dlo_a = (((sb + cw * 8192) & 0x3FFFF) >> 4) | (1u << 16);
    const uint32_t dlo_b = (((sb + WB) & 0x3FFFF) >> 4) | ((4096u >> 4) << 16);
    const int trb = 200 + 100 * cw;
    const bool lead = cw == LEADWG;
    Ring rg = {0, 0, 0, 0u, 0u};
    const int srow = (lane & 7) + 8 * ((lane >> 3) & 1);
    const int prow = 32 * (w8 >> 1) + 2 * (lane >> 2) + (w8 & 1);
    const uint32_t rel = mapa(bar + 8 * (lane < 2 ? B_WE : B_AE), lane == 1 ? 1 - r : r);
    const uint32_t bias = sb + BIAS_OFF + 16 * (lane >> 3);
    auto nomid = [](auto) {};
    float hacc[108];
#pragma unroll
    for (int g8 = 0; g8 < 27; g8++) { hacc[4 * g8] = hacc[4 * g8 + 2] = bf_lo(bw[g8]); hacc[4 * g8 + 1] = hacc[4 * g8 + 3] = bf_hi(bw[g8]); }
    fence_regs<108>(hacc);
    TC(tc1);
    cluster_wait();
    TC(tc2);
    mbar_wait(bar + 8 * B_AF, 0, rg.spin);
    mbar_wait(bar + 8 * B_WF, 0, rg.spin);
    auto nohook = [](int) {};
    auto notail = []() {};
    auto one_minus_g = [&](uint32_t& om0, uint32_t& om1) {
      const float g0 = __uint_as_float(lds16(sb + G_OFF + 2 * prow) << 16), g1 = __uint_as_float(lds16(sb + G_OFF + 2 * (prow + 16)) << 16);
      om0 = pack_bf16(1.f - g0, 1.f - g0); om1 = pack_bf16(1.f - g1, 1.f - g1);
    };
    uint32_t hp[54];
    uint32_t om0 = 0, om1 = 0;
    {
      mma_loop<0>(hacc, rg, bar, rel, dlo_a, dlo_b, 0, 0, lane, lead, trb, nomid, nohook, nohook, notail);
      if ((w8 & 3) == 0 && lane == 0) TR(400 + 20 * cw);
      mbar_wait(bar + 8 * B_GREADY, 0, rg.spin);
      one_minus_g(om0, om1);
#pragma unroll
      for (int e = 0; e < 54; e++) hp[e] = pack_bf16_relu(hacc[2 * e], hacc[2 * e + 1]);
      if ((w8 & 3) == 0 && lane == 0) TR(400 + 20 * cw + 1);
    }
    uint32_t hsa = sb + R0 + (16 * w8 + srow) * 128, hx4 = (uint32_t)(((lane >> 4) ^ (srow & 7)) << 4);
    auto h_group = [&](auto gc) {
      constexpr int g32 = decltype(gc)::value;
      uint32_t v[8];
#pragma unroll
      for (int e = 0; e < (g32 < 6 ? 8 : 6); e++) v[e] = mul_bf16x2(mul_bf16x2(hp[8 * g32 + e], hp[8 * g32 + e]), (e & 1) ? om1 : om0);
      if (g32 < 6) {
#pragma unroll
        for (int e = 0; e < 2; e++) {
          const int g8 = 4 * g32 + 2 * e;
          stmatrix_x4(hsa + (g8 >> 3) * 16384 + ((uint32_t)((g8 & 7) << 4) ^ hx4), v[4 * e], v[4 * e + 1], v[4 * e + 2], v[4 * e + 3]);
        }
      } else {
        uint32_t* hn = reinterpret_cast<uint32_t*>(g_H) + (uint32_t)((128 * i + 16 * w8 + (lane >> 2)) * (FF / 2) + 768 + 12 * j + (lane & 3));
#pragma unroll
        for (int e = 0; e < 6; e++) hn[(e & 1) * 8 * (FF / 2) + 4 * (e >> 1)] = v[e];
      }
      if ((g32 & 1) || g32 == 6) {
        __syncwarp();
        if (lane == 0) mbar_arrive(bar + 8 * (B_HDONE + (g32 >> 1)));
      }
    };
    h_group(IC<0>{}); h_group(IC<1>{}); h_group(IC<2>{}); h_group(IC<3>{}); h_group(IC<4>{}); h_group(IC<5>{});
    if ((w8 & 3) == 0 && lane == 0) TR(400 + 20 * cw + 1);
    uint32_t q[20];
    const uint32_t kplane = sb + R0 + (w8 & 1) * PLANE + roff(16 * (w8 >> 1));
    {
      float acc[120];
      mma_loop<1>(acc, rg, bar, rel, dlo_a, dlo_b, sb + cw * 8192 + (16 * (w8 & 3) + srow) * 128, (uint32_t)(((lane >> 4) ^ (srow & 7)) << 4), lane, lead, trb + N_H, nomid, [&](int m) {
        if (m == G6POS) h_group(IC<6>{});
      }, [&](int m) {
      }, notail);
      if ((w8 & 3) == 0 && lane == 0) TR(400 + 20 * cw + 2);
      if (w8 >= 6) {
        const uint32_t tag = lds32(sb + TAG_OFF);
        ulonglong2* hp = g_halo + ((cs * 2 + (w8 & 1)) * 320 + lane);
#pragma unroll
        for (int c = 0; c < 10; c++) {
          const int g8 = c % 5 < 4 ? 8 + 8 * (c / 5) + 2 * (c % 5) : 26 + 2 * (c / 5);
          st_ll2(hp + 32 * c, pack_bf16(acc[4 * g8 + 2], acc[4 * g8 + 3]), pack_bf16(acc[4 * g8 + 6], acc[4 * g8 + 7]), tag);
        }
        if (lane == 0) { st_relaxed(g_flag + i * 32 + 16 + 2 * j + (w8 & 1), tag); mbar_arrive(bar + 8 * B_KV); }
      }
      mbar_wait(bar + 8 * B_HFREE, 0, rg.spin);
      const uint32_t ka = kplane + roff(8 + srow) + (lane >> 4) * 16;
#pragma unroll
      for (int X = 0; X < 2; X++)
#pragma unroll
        for (int c = 0; c < 5; c++) {
          const int g8 = c < 4 ? 8 + 8 * X + 2 * c : 26 + 2 * X;
          stmatrix_x4(ka + X * 2 * PLANE + c * 32, pack_bf16(acc[4 * g8], acc[4 * g8 + 1]), pack_bf16(acc[4 * g8 + 2], acc[4 * g8 + 3]),
                      pack_bf16(acc[4 * g8 + 4], acc[4 * g8 + 5]), pack_bf16(acc[4 * g8 + 6], acc[4 * g8 + 7]));
        }
#pragma unroll
      for (int c = 0; c < 10; c++) {
        const int g8 = c < 8 ? c : 16 + c;
        q[2 * c] = pack_bf16(acc[4 * g8], acc[4 * g8 + 1]); q[2 * c + 1] = pack_bf16(acc[4 * g8 + 2], acc[4 * g8 + 3]);
      }
      if ((w8 & 3) == 0 && lane == 0) TR(400 + 20 * cw + 3);
    }
    float acc[80];
    uint32_t b2[20];
    mma_loop<2>(acc, rg, bar, rel, dlo_a, dlo_b, 0, 0, lane, lead, trb + N_H + N_QKV, [&](auto drain) {
      if ((w8 & 3) == 0 && lane == 0) TR(400 + 20 * cw + 4);
      mbar_wait(bar + 8 * B_HALO, 0, rg.spin);
      asm volatile("bar.sync 1, 256;" ::: "memory");
      if ((w8 & 3) == 0 && lane == 0) TR(400 + 20 * cw + 5);
      const float g0 = __uint_as_float(lds16(sb + G_OFF + 2 * prow) << 16), g1 = __uint_as_float(lds16(sb + G_OFF + 2 * (prow + 16)) << 16);
      attention(q, kplane, lane, i == 0 && w8 < 2, g0, g1, drain);
      asm volatile("bar.sync 1, 256;" ::: "memory");
      const uint32_t oa = sb + R0 + (16 * w8 + srow) * 160 + (lane >> 4) * 16;
#pragma unroll
      for (int c = 0; c < 5; c++) stmatrix_x4(oa + c * 32, q[4 * c], q[4 * c + 1], q[4 * c + 2], q[4 * c + 3]);
      __syncwarp();
      if (lane == 0) mbar_arrive(bar + 8 * B_ODONE);
      if ((w8 & 3) == 0 && lane == 0) TR(400 + 20 * cw + 6);
    }, [&](int m) {
    }, nohook, [&]() {
      one_minus_g(om0, om1);
      if (kh != 0) { om0 = 0; om1 = 0; }
#pragma unroll
      for (int g32 = 0; g32 < 5; g32++) ldsm4(b2 + 4 * g32, bias + 64 * g32);
      fence_async_glob();
    });
    if ((w8 & 3) == 0 && lane == 0) TR(400 + 20 * cw + 7);
    {
      const uint32_t st = sb + R0 + w8 * 5120;
      const uint32_t sa = st + srow * 128, x4 = (uint32_t)(((lane >> 4) ^ (srow & 7)) << 4);
      const uint32_t sn = st + 4096 + srow * 64, xn = (uint32_t)(((lane >> 4) ^ ((srow >> 1) & 3)) << 4);
      const int c2 = w8 & 1, c3 = 4 * i + (w8 >> 1);
#pragma unroll
      for (int g32 = 0; g32 < 5; g32++) {
        const uint32_t* b = b2 + 4 * g32;
        uint32_t v[8];
#pragma unroll
        for (int e = 0; e < 8; e++) v[e] = fma_bf16x2((e & 1) ? om1 : om0, b[e >> 1], pack_bf16(acc[16 * g32 + 2 * e], acc[16 * g32 + 2 * e + 1]));
#pragma unroll
        for (int e = 0; e < 2; e++) {
          const int g8 = 4 * g32 + 2 * e;
          stmatrix_x4(g8 < 16 ? sa + (g8 >> 3) * 2048 + ((uint32_t)((g8 & 7) << 4) ^ x4) : sn + ((uint32_t)((g8 & 3) << 4) ^ xn), v[4 * e], v[4 * e + 1], v[4 * e + 2], v[4 * e + 3]);
        }
        if (TAILSPLIT > 1 && g32 == 1 || TAILSPLIT > 2 && g32 == 3) {
          fence_async_smem();
          __syncwarp();
          if (elect_one()) tma_reduce_4d(&p.outw, st + (g32 >> 1) * 2048, 128 * t + 64 * (g32 >> 1), c2, c3);
        }
      }
      if ((w8 & 3) == 0 && lane == 0) TR(400 + 20 * cw + 9);
      fence_async_smem();
      __syncwarp();
      if ((w8 & 3) == 0 && lane == 0) TR(400 + 20 * cw + 10);
      if (elect_one()) {
        if (TAILSPLIT < 2) tma_reduce_4d(&p.outw, st, 128 * t, c2, c3);
        if (TAILSPLIT < 3) tma_reduce_4d(&p.outw, st + 2048, 128 * t + 64, c2, c3);
        tma_reduce_4d(&p.outn, st + 4096, 512 + 32 * t, c2, c3);
        asm volatile("cp.async.bulk.commit_group;" ::: "memory");
        if ((w8 & 3) == 0) TR(400 + 20 * cw + 11);
        asm volatile("cp.async.bulk.wait_group.read 0;" ::: "memory");
      }
      __syncwarp();
    }
    if ((w8 & 3) == 0 && lane == 0) TR(400 + 20 * cw + 8);
    if (tid == 128) atomicAdd(&g_done, 1u);
  }
}

typedef CUresult (*PFN_encodeTiled)(CUtensorMap*, CUtensorMapDataType, cuuint32_t, void*, const cuuint64_t*, const cuuint64_t*,
                                    const cuuint32_t*, const cuuint32_t*, CUtensorMapInterleave, CUtensorMapSwizzle,
                                    CUtensorMapL2promotion, CUtensorMapFloatOOBfill);

void encode(PFN_encodeTiled fn, CUtensorMap* m, const void* base, int rank, const cuuint64_t* dims, const cuuint64_t* strides,
            const cuuint32_t* box, CUtensorMapSwizzle swz) {
  cuuint32_t es[5] = {1, 1, 1, 1, 1};
  fn(m, CU_TENSOR_MAP_DATA_TYPE_BFLOAT16, rank, const_cast<void*>(base), dims, strides, box, es, CU_TENSOR_MAP_INTERLEAVE_NONE, swz,
     CU_TENSOR_MAP_L2_PROMOTION_L2_128B, CU_TENSOR_MAP_FLOAT_OOB_FILL_NONE);
}
void encode4d(PFN_encodeTiled fn, CUtensorMap* m, const void* base, uint64_t d0, uint64_t d1, uint64_t d2, uint64_t d3, uint64_t s1, uint64_t s2, uint64_t s3,
              uint32_t b0, uint32_t b1, uint32_t b2, uint32_t b3, CUtensorMapSwizzle swz) {
  cuuint64_t dims[4] = {d0, d1, d2, d3}; cuuint64_t st[3] = {s1, s2, s3}; cuuint32_t box[4] = {b0, b1, b2, b3};
  encode(fn, m, base, 4, dims, st, box, swz);
}

}

extern "C" void kernel_launch(void* const* d_in, const int* in_sizes, int n_in, void* d_out, int out_size) {
  static Params prm;
  static void* cached[10] = {};
  static bool attr_done = false;
  bool same = attr_done;
  for (int k = 0; k < 9; k++) same = same && cached[k] == d_in[k];
  same = same && cached[9] == d_out;
  if (!same) {
    void* fnp = nullptr;
    cudaDriverEntryPointQueryResult qr;
    cudaGetDriverEntryPoint("cuTensorMapEncodeTiled", &fnp, cudaEnableDefault, &qr);
    PFN_encodeTiled fn = (PFN_encodeTiled)fnp;
    const __nv_bfloat16* ax = (const __nv_bfloat16*)d_in[0];
    const __nv_bfloat16* wqkv = (const __nv_bfloat16*)d_in[1];
    const __nv_bfloat16* wo = (const __nv_bfloat16*)d_in[2];
    const __nv_bfloat16* w1 = (const __nv_bfloat16*)d_in[4];
    const __nv_bfloat16* w2 = (const __nv_bfloat16*)d_in[6];
    void *hp = nullptr, *op = nullptr;
    cudaGetSymbolAddress(&hp, g_H);
    cudaGetSymbolAddress(&op, g_O);
    const CUtensorMapSwizzle S128 = CU_TENSOR_MAP_SWIZZLE_128B, S64 = CU_TENSOR_MAP_SWIZZLE_64B, S0 = CU_TENSOR_MAP_SWIZZLE_NONE;
    encode4d(fn, &prm.a[0], ax, DM, 16, 2, SEQ / 32, 2 * DM * 2, DM * 2, 32 * DM * 2, 64, 16, 2, 4, S128);
    encode4d(fn, &prm.a[1], hp, FF, 16, 2, SEQ / 32, FF * 2, 16 * FF * 2, 32 * FF * 2, 64, 16, 2, 4, S128);
    encode4d(fn, &prm.a[2], op, DM, 16, 2, SEQ / 32, DM * 2, 16 * DM * 2, 32 * DM * 2, 64, 16, 2, 4, S128);
    encode4d(fn, &prm.hst, hp, FF, 16, 2, SEQ / 32, FF * 2, 16 * FF * 2, 32 * FF * 2, 64, 16, 2, 1, S128);
    encode4d(fn, &prm.ost, op, DM, 16, 2, SEQ / 32, DM * 2, 16 * DM * 2, 32 * DM * 2, 80, 16, 2, 4, S0);
    encode4d(fn, &prm.outw, d_out, DM, 16, 2, SEQ / 32, 2 * DM * 2, DM * 2, 32 * DM * 2, 64, 16, 1, 1, S128);
    encode4d(fn, &prm.outn, d_out, DM, 16, 2, SEQ / 32, 2 * DM * 2, DM * 2, 32 * DM * 2, 32, 16, 1, 1, S64);
    encode4d(fn, &prm.w[0], w1, 64, DM, 3, 8, FF * 2, 128, 384, 64, 32, 3, 1, S128);
    encode4d(fn, &prm.w[1], w1 + 1536, 24, DM, 1, 8, FF * 2, 128, 48, NBOX1, 32, 1, 1, S128);
    encode4d(fn, &prm.w[2], wqkv, 64, DM, 3, 8, 3 * DM * 2, DM * 2, 160, 64, 32, 3, 1, S128);
    encode4d(fn, &prm.w[3], wqkv + 64, 16, DM, 3, 8, 3 * DM * 2, DM * 2, 160, 16, 32, 3, 1, CU_TENSOR_MAP_SWIZZLE_32B);
    encode4d(fn, &prm.w[4], w2, 64, FF, 2, 4, DM * 2, 128, 256, 64, 32, 2, 1, S128);
    encode4d(fn, &prm.w[5], w2 + 512, 32, FF, 1, 4, DM * 2, 128, 64, NBOX2, 32, 1, 1, S128);
    encode4d(fn, &prm.w[6], wo, 64, DM, 2, 4, DM * 2, 128, 256, 64, 32, 2, 1, S128);
    encode4d(fn, &prm.w[7], wo + 512, 32, DM, 1, 4, DM * 2, 128, 64, NBOX2, 32, 1, 1, S128);
    prm.pwqkv = wqkv; prm.pwo = wo; prm.pw2 = w2;
    cudaFuncSetAttribute(fused_kernel, cudaFuncAttributeMaxDynamicSharedMemorySize, SMEM_BYTES);
    for (int k = 0; k < 9; k++) cached[k] = d_in[k];
    cached[9] = d_out;
    attr_done = true;
  }
  cudaLaunchConfig_t cfg = {};
  cfg.gridDim = dim3(NCTA);
  cfg.blockDim = dim3(NTHREADS);
  cfg.dynamicSmemBytes = SMEM_BYTES;
  cfg.stream = cudaStreamPerThread;
  cudaLaunchKernelEx(&cfg, fused_kernel, (const __nv_bfloat16*)d_in[0], (const __nv_bfloat16*)d_in[4], (const __nv_bfloat16*)d_in[5],
                     (const __nv_bfloat16*)d_in[8], (__nv_bfloat16*)d_out, (const __nv_bfloat16*)d_in[7], prm);
}
```
